```python
import torch

def _softmax(x, axis=-1):
    return torch.softmax(x, dim=axis)
def _gelu(x):
    return torch.nn.functional.gelu(x, approximate="tanh")
def _silu(x):
    return torch.nn.functional.silu(x)
def _sigmoid(x):
    return torch.sigmoid(x)
def _layernorm(x, axis=-1, eps=1e-5):
    m = x.mean(dim=axis, keepdim=True)
    v = x.var(dim=axis, keepdim=True, unbiased=False)
    return (x - m) / torch.sqrt(v + eps)
def _scatter_add(tgt, idx, src, axis=0):
    return tgt.clone().index_add_(axis, idx, src)
def _segment_sum(src, seg, n):
    out = torch.zeros((n,) + src.shape[1:], dtype=src.dtype)
    return out.index_add_(0, seg, src)
def _pad(x, pw):
    flat = tuple(v for pair in reversed(pw) for v in pair)
    return torch.nn.functional.pad(x, flat)

kernel_name = 'recurrent_scan__ssm_conv_s4d__dense_activation_squared_relu__prompt'

def setup_inputs():

    _w = (lambda a: (lambda t: t.to(torch.bfloat16) if t.is_floating_point() else t)(torch.as_tensor(a)))
    def _A_setup():
        Bsz, L, D, N = 1, 2048, 512, 128
        return {
            "u": _w((lambda *s: torch.randn(*s, dtype=torch.bfloat16) * 0.05)(Bsz, L, D)),
            "log_A_real": _w((lambda *s: torch.randn(*s, dtype=torch.bfloat16) * 3.2)(D, N) * 0.5),
            "A_imag": _w((lambda *s: torch.randn(*s, dtype=torch.bfloat16) * 0.05)(D, N) * 3.14),
            "C_real": _w((lambda *s: torch.randn(*s, dtype=torch.bfloat16) * 0.2)(D, N) / N ** 0.5),
            "C_imag": _w((lambda *s: torch.randn(*s, dtype=torch.bfloat16) * 0.2)(D, N) / N ** 0.5),
            "log_dt": _w((lambda *s: torch.randn(*s, dtype=torch.bfloat16) * 0.05)(D) * 0.5 - 4.0),
            "D_skip": _w((lambda *s: torch.randn(*s, dtype=torch.bfloat16) * 0.05)(D)),
        }
    _A_in = _A_setup()

    def _B_setup():
        B, S, D, F = 1, 2048, 512, 1792
        return {
            "x": _w((lambda *s: torch.randn(*s, dtype=torch.bfloat16) * 0.05)(B, S, D)),
            "w1": _w((lambda *s: torch.randn(*s, dtype=torch.bfloat16) * 0.05)(D, F)),
            "b1": _w((lambda *s: torch.randn(*s, dtype=torch.bfloat16) * 0.4)(F)),
            "w2": _w((lambda *s: torch.randn(*s, dtype=torch.bfloat16) * 0.05)(F, D)),
            "b2": _w((lambda *s: torch.randn(*s, dtype=torch.bfloat16) * 0.8)(D)),
        }
    _B_in = _B_setup()

    return {
        "A_u": _A_in["u"],
        "A_log_A_real": _A_in["log_A_real"],
        "A_A_imag": _A_in["A_imag"],
        "A_C_real": _A_in["C_real"],
        "A_C_imag": _A_in["C_imag"],
        "A_log_dt": _A_in["log_dt"],
        "A_D_skip": _A_in["D_skip"],
        "B_x": _B_in["x"],
        "B_w1": _B_in["w1"],
        "B_b1": _B_in["b1"],
        "B_w2": _B_in["w2"],
        "B_b2": _B_in["b2"],
    }

def reference(A_u, A_log_A_real, A_A_imag, A_C_real, A_C_imag, A_log_dt, A_D_skip, B_x, B_w1, B_b1, B_w2, B_b2):
    def _A_ref(u, log_A_real, A_imag, C_real, C_imag, log_dt, D_skip):
        L = u.shape[1]
        dt = torch.exp(log_dt)
        A = -torch.exp(log_A_real) + 1j * A_imag
        C = (C_real + 1j * C_imag) * dt[:, None]
        pos = (lambda x, dt: x.to(dt))(torch.arange(L), log_dt.dtype)
        P = torch.exp((A * dt[:, None])[:, :, None] * pos[None, None, :])
        K = 2.0 * torch.einsum("dn,dnl->dl", C, P).real
        L2 = 2 * L
        u_t = (lambda x, *d: x.permute(*d))(u, 0, 2, 1)
        Kf = (lambda x, *a, **k: torch.fft.rfft(x.float(), *a, **k))(K, L2)
        Uf = (lambda x, *a, **k: torch.fft.rfft(x.float(), *a, **k))(u_t, L2)
        y = (lambda x, *a, **k: torch.fft.irfft(x, *a, **k).to(torch.bfloat16))(Uf * Kf[None, :, :], L2)[:, :, :L]
        y = (lambda x, *d: x.permute(*d))(y, 0, 2, 1)
        return y + u * D_skip[None, None, :]

    def _B_ref(x, w1, b1, w2, b2):
        h = torch.einsum("bsd,df->bsf", x, w1) + b1
        zero = torch.zeros_like(h)
        r = torch.where(h > zero, h, zero)
        h = r * r
        out = torch.einsum("bsf,fd->bsd", h, w2) + b2
        return out

    x = A_u
    xn = _layernorm(x, axis=-1)
    s = _A_ref(xn, A_log_A_real, A_A_imag, A_C_real, A_C_imag, A_log_dt, A_D_skip)
    g = _silu(_B_ref(xn, B_w1, B_b1, B_w2, B_b2))
    return x + s * g
```

```cpp
#include <cuda_runtime.h>
#include <cuda_bf16.h>
#include <cuda_fp16.h>
#include <cuda.h>
#include <stdint.h>

constexpr int L_SEQ = 2048;
constexpr int D_MODEL = 512;
constexpr int N_STATE = 128;
constexpr int F_HID = 1792;

__device__ __align__(1024) __nv_bfloat16 g_xn[L_SEQ * D_MODEL];
__device__ __align__(1024) __nv_bfloat16 g_h[L_SEQ * F_HID];
__device__ __align__(1024) __nv_bfloat16 g_s[L_SEQ * D_MODEL];
__device__ __align__(1024) float g_K[D_MODEL * L_SEQ];

__device__ __forceinline__ float bf16r(float x) { return __bfloat162float(__float2bfloat16_rn(x)); }

__device__ __forceinline__ uint32_t smem_u32(const void* p) {
    return (uint32_t)__cvta_generic_to_shared(p);
}
__device__ __forceinline__ void mbar_init(uint32_t bar, uint32_t count) {
    asm volatile("mbarrier.init.shared::cta.b64 [%0], %1;" ::"r"(bar), "r"(count));
}
__device__ __forceinline__ void mbar_expect_tx(uint32_t bar, uint32_t bytes) {
    asm volatile("mbarrier.arrive.expect_tx.shared::cta.b64 _, [%0], %1;" ::"r"(bar), "r"(bytes) : "memory");
}
__device__ __forceinline__ void mbar_arrive(uint32_t bar) {
    asm volatile("mbarrier.arrive.shared::cta.b64 _, [%0];" ::"r"(bar) : "memory");
}
__device__ __forceinline__ bool mbar_try_wait(uint32_t bar, uint32_t parity) {
    uint32_t ok;
    asm volatile(
        "{\n"
        ".reg .pred p;\n"
        "mbarrier.try_wait.parity.shared::cta.b64 p, [%1], %2;\n"
        "selp.u32 %0, 1, 0, p;\n"
        "}\n" : "=r"(ok) : "r"(bar), "r"(parity) : "memory");
    return ok != 0;
}
__device__ __forceinline__ void mbar_wait(uint32_t bar, uint32_t parity) {
    if (mbar_try_wait(bar, parity)) return;
    for (int it = 0; it < (1 << 24); it++) {
        if (mbar_try_wait(bar, parity)) return;
    }
    __trap();
}
__device__ __forceinline__ void tma_load_2d(uint32_t smem_dst, const CUtensorMap* tm, uint32_t bar, int c0, int c1) {
    asm volatile(
        "cp.async.bulk.tensor.2d.shared::cluster.global.mbarrier::complete_tx::bytes [%0], [%1, {%3, %4}], [%2];"
        ::"r"(smem_dst), "l"((uint64_t)tm), "r"(bar), "r"(c0), "r"(c1) : "memory");
}
__device__ __forceinline__ void wgmma_fence() { asm volatile("wgmma.fence.sync.aligned;" ::: "memory"); }
__device__ __forceinline__ void wgmma_commit() { asm volatile("wgmma.commit_group.sync.aligned;" ::: "memory"); }
template <int N>
__device__ __forceinline__ void wgmma_wait() { asm volatile("wgmma.wait_group.sync.aligned %0;" ::"n"(N) : "memory"); }

__device__ __forceinline__ uint64_t make_desc(uint32_t saddr, uint32_t lbo_bytes, uint32_t sbo_bytes) {
    uint64_t d = 0;
    d |= (uint64_t)((saddr & 0x3FFFF) >> 4);
    d |= (uint64_t)((lbo_bytes & 0x3FFFF) >> 4) << 16;
    d |= (uint64_t)((sbo_bytes & 0x3FFFF) >> 4) << 32;
    d |= (uint64_t)1 << 62;
    return d;
}

__device__ __forceinline__ void wgmma_m64n64k16(float (&d)[32], uint64_t da, uint64_t db) {
    asm volatile(
        "{\n"
        ".reg .pred p;\n"
        "setp.ne.b32 p, %34, 0;\n"
        "wgmma.mma_async.sync.aligned.m64n64k16.f32.bf16.bf16 "
        "{%0,%1,%2,%3,%4,%5,%6,%7,%8,%9,%10,%11,%12,%13,%14,%15,"
        "%16,%17,%18,%19,%20,%21,%22,%23,%24,%25,%26,%27,%28,%29,%30,%31},"
        " %32, %33, p, 1, 1, 0, 1;\n"
        "}\n"
        : "+f"(d[0]), "+f"(d[1]), "+f"(d[2]), "+f"(d[3]), "+f"(d[4]), "+f"(d[5]), "+f"(d[6]), "+f"(d[7]),
          "+f"(d[8]), "+f"(d[9]), "+f"(d[10]), "+f"(d[11]), "+f"(d[12]), "+f"(d[13]), "+f"(d[14]), "+f"(d[15]),
          "+f"(d[16]), "+f"(d[17]), "+f"(d[18]), "+f"(d[19]), "+f"(d[20]), "+f"(d[21]), "+f"(d[22]), "+f"(d[23]),
          "+f"(d[24]), "+f"(d[25]), "+f"(d[26]), "+f"(d[27]), "+f"(d[28]), "+f"(d[29]), "+f"(d[30]), "+f"(d[31])
        : "l"(da), "l"(db), "r"(1));
}

__global__ void __launch_bounds__(256) ln_kernel(const __nv_bfloat16* __restrict__ x) {
    int warp = (blockIdx.x * blockDim.x + threadIdx.x) >> 5;
    int lane = threadIdx.x & 31;
    if (warp >= L_SEQ) return;
    const uint4* xr = reinterpret_cast<const uint4*>(x + (size_t)warp * D_MODEL);
    float v[16];
#pragma unroll
    for (int i = 0; i < 2; i++) {
        uint4 t = xr[lane + 32 * i];
        const __nv_bfloat162* p = reinterpret_cast<const __nv_bfloat162*>(&t);
#pragma unroll
        for (int j = 0; j < 4; j++) {
            float2 f = __bfloat1622float2(p[j]);
            v[i * 8 + 2 * j] = f.x;
            v[i * 8 + 2 * j + 1] = f.y;
        }
    }
    float s = 0.f;
#pragma unroll
    for (int i = 0; i < 16; i++) s += v[i];
#pragma unroll
    for (int o = 16; o > 0; o >>= 1) s += __shfl_xor_sync(0xffffffffu, s, o);
    float mean = s * (1.0f / D_MODEL);
    float q = 0.f;
#pragma unroll
    for (int i = 0; i < 16; i++) { float d = v[i] - mean; q += d * d; }
#pragma unroll
    for (int o = 16; o > 0; o >>= 1) q += __shfl_xor_sync(0xffffffffu, q, o);
    float var = bf16r(q * (1.0f / D_MODEL));
    float mb = bf16r(mean);
    float sd = bf16r(sqrtf(bf16r(var + 1e-5f)));
    uint4* outr = reinterpret_cast<uint4*>(g_xn + (size_t)warp * D_MODEL);
#pragma unroll
    for (int i = 0; i < 2; i++) {
        uint4 t;
        __nv_bfloat162* p = reinterpret_cast<__nv_bfloat162*>(&t);
#pragma unroll
        for (int j = 0; j < 4; j++) {
            float a = bf16r(v[i * 8 + 2 * j] - mb) / sd;
            float b = bf16r(v[i * 8 + 2 * j + 1] - mb) / sd;
            p[j] = __floats2bfloat162_rn(a, b);
        }
        outr[lane + 32 * i] = t;
    }
}

__device__ __forceinline__ float2 cexp_f(float re, float im) {
    float e = expf(re);
    float s, c;
    sincosf(im, &s, &c);
    return make_float2(e * c, e * s);
}
__device__ __forceinline__ float2 cmul(float2 a, float2 b) {
    return make_float2(a.x * b.x - a.y * b.y, a.x * b.y + a.y * b.x);
}

__global__ void __launch_bounds__(128) kgen_kernel(const __nv_bfloat16* __restrict__ logAr,
                                                   const __nv_bfloat16* __restrict__ Aim,
                                                   const __nv_bfloat16* __restrict__ Cre,
                                                   const __nv_bfloat16* __restrict__ Cim,
                                                   const __nv_bfloat16* __restrict__ logdt) {
    extern __shared__ float2 sm[];
    float2* W = sm;
    float2* Z = sm + 17 * 128;
    __shared__ float Kd[648];
    int d = blockIdx.x;
    int n = threadIdx.x;
    float dt = bf16r(expf(__bfloat162float(logdt[d])));
    float ar = -bf16r(expf(__bfloat162float(logAr[d * N_STATE + n])));
    float ai = __bfloat162float(Aim[d * N_STATE + n]);
    float are = ar * dt, aim = ai * dt;
    float2 C = make_float2(__bfloat162float(Cre[d * N_STATE + n]) * dt, __bfloat162float(Cim[d * N_STATE + n]) * dt);

    for (int r = 0; r < 4; r++) {
        int base = (r == 0) ? 0 : (128 << r);
        int step = 1 << r;
        int nhi = (r == 0) ? 16 : ((r == 3) ? 9 : 8);
        for (int lo = 0; lo < 16; lo++) {
            float p = (float)(step * lo);
            Z[lo * 128 + n] = cexp_f(are * p, aim * p);
        }
        for (int hi = 0; hi < nhi; hi++) {
            float p = (float)(base + 16 * step * hi);
            W[hi * 128 + n] = cmul(C, cexp_f(are * p, aim * p));
        }
        __syncthreads();
        int npos = (r == 0) ? 256 : ((r == 3) ? 129 : 128);
        int obase = (r == 0) ? 0 : (256 + (r - 1) * 128);
        for (int i = threadIdx.x; i < npos; i += 128) {
            int hi = i >> 4, lo = i & 15;
            float acc = 0.f;
            for (int m = 0; m < 128; m++) {
                float2 w = W[hi * 128 + m], z = Z[lo * 128 + m];
                acc += w.x * z.x - w.y * z.y;
            }
            Kd[obase + i] = 2.0f * acc;
        }
        __syncthreads();
    }
    for (int j = threadIdx.x; j < L_SEQ; j += 128) {
        int p = (int)__bfloat162float(__float2bfloat16_rn((float)j));
        int idx;
        if (p < 256) idx = p;
        else if (p < 512) idx = 256 + ((p - 256) >> 1);
        else if (p < 1024) idx = 384 + ((p - 512) >> 2);
        else idx = 512 + ((p - 1024) >> 3);
        g_K[d * L_SEQ + j] = Kd[idx];
    }
}

constexpr int CB = 64;
constexpr int CONV_CH = 4;
constexpr int KP_LEN = L_SEQ + CB + 32;
constexpr int UR_BLK = 72;
constexpr int UR_NBLK = (L_SEQ + 512) / CB;
struct ConvSmem {
    __half kpE[CONV_CH][KP_LEN];
    __half kpO[CONV_CH][KP_LEN + 32];
    __half ur[CONV_CH][UR_NBLK * UR_BLK];
};

__device__ __forceinline__ void mma_16816(float (&c)[4], uint32_t a0, uint32_t a1, uint32_t a2, uint32_t a3,
                                          uint32_t b0, uint32_t b1) {
    asm volatile(
        "mma.sync.aligned.m16n8k16.row.col.f32.f16.f16.f32 {%0,%1,%2,%3}, {%4,%5,%6,%7}, {%8,%9}, {%0,%1,%2,%3};"
        : "+f"(c[0]), "+f"(c[1]), "+f"(c[2]), "+f"(c[3])
        : "r"(a0), "r"(a1), "r"(a2), "r"(a3), "r"(b0), "r"(b1));
}

__global__ void __launch_bounds__(256) conv_kernel(const __nv_bfloat16* __restrict__ Dskip) {
    extern __shared__ __align__(16) unsigned char smraw[];
    ConvSmem& S = *reinterpret_cast<ConvSmem*>(smraw);
    __shared__ float sscale[CONV_CH];
    __shared__ float sred[8];
    const int d0 = blockIdx.x * CONV_CH;
    const int tid = threadIdx.x, warp = tid >> 5, lane = tid & 31;

    for (int c = 0; c < CONV_CH; c++) {
        float mx = 0.f;
        for (int j = tid; j < L_SEQ; j += 256) mx = fmaxf(mx, fabsf(g_K[(d0 + c) * L_SEQ + j]));
#pragma unroll
        for (int o = 16; o > 0; o >>= 1) mx = fmaxf(mx, __shfl_xor_sync(0xffffffffu, mx, o));
        if (lane == 0) sred[warp] = mx;
        __syncthreads();
        if (tid == 0) {
            float m = 0.f;
            for (int w = 0; w < 8; w++) m = fmaxf(m, sred[w]);
            int e = 0;
            if (m > 0.f && isfinite(m)) { frexpf(m, &e); }
            sscale[c] = (m > 0.f && isfinite(m)) ? ldexpf(1.0f, 10 - e) : 1.0f;
        }
        __syncthreads();
    }
    for (int c = 0; c < CONV_CH; c++) {
        float sc = sscale[c];
        for (int t = tid; t < KP_LEN; t += 256) {
            int j0 = t - (CB - 1), j1 = j0 + 1;
            float v0 = (j0 >= 0 && j0 < L_SEQ) ? g_K[(d0 + c) * L_SEQ + j0] * sc : 0.f;
            float v1 = (j1 >= 0 && j1 < L_SEQ) ? g_K[(d0 + c) * L_SEQ + j1] * sc : 0.f;
            S.kpE[c][t] = __float2half_rn(v0);
            S.kpO[c][t] = __float2half_rn(v1);
        }
    }
    for (int r = tid; r < UR_NBLK * CB; r += 256) {
        int l = L_SEQ - 1 - r;
        int pos = (r / CB) * UR_BLK + (r % CB);
        if (l >= 0) {
            uint2 t = *reinterpret_cast<const uint2*>(g_xn + (size_t)l * D_MODEL + d0);
            const __nv_bfloat16* p = reinterpret_cast<const __nv_bfloat16*>(&t);
#pragma unroll
            for (int c = 0; c < CONV_CH; c++) S.ur[c][pos] = __float2half_rn(__bfloat162float(p[c]));
        } else {
#pragma unroll
            for (int c = 0; c < CONV_CH; c++) S.ur[c][pos] = __float2half_rn(0.f);
        }
    }
    __syncthreads();

    const int c = warp >> 1;
    const int half = warp & 1;
    const int g = lane >> 2, t4 = lane & 3;
    const __half* kp = (g & 1) ? &S.kpO[c][0] : &S.kpE[c][0];
    const int goff = (g & 1) ? (g - 1) : g;
    const float inv_sc = 1.0f / sscale[c];
    const float dsk = __bfloat162float(Dskip[d0 + c]);

    for (int pass = 0; pass < 2; pass++) {
        int nt = half ? (pass == 0 ? 1 : 2) : (pass == 0 ? 0 : 3);
        int a0 = nt * 8;
        float acc[4][4];
#pragma unroll
        for (int mi = 0; mi < 4; mi++)
#pragma unroll
            for (int k = 0; k < 4; k++) acc[mi][k] = 0.f;
        int nk = 32 * (nt + 1);
        uint32_t Plo[5], Phi[4];
#pragma unroll
        for (int s = 0; s < 5; s++) Plo[s] = *reinterpret_cast<const uint32_t*>(kp + 16 * s + 2 * t4 + goff);
#pragma unroll
        for (int s = 0; s < 4; s++) Phi[s] = *reinterpret_cast<const uint32_t*>(kp + 16 * s + 8 + 2 * t4 + goff);
        for (int ki = 0; ki < nk; ki++) {
            int r = L_SEQ - (a0 + g + 1) * CB + 16 * ki;
            int pos = (r / CB) * UR_BLK + (r % CB) + 2 * t4;
            uint32_t b0 = *reinterpret_cast<const uint32_t*>(&S.ur[c][pos]);
            uint32_t b1 = *reinterpret_cast<const uint32_t*>(&S.ur[c][pos + 8]);
#pragma unroll
            for (int mi = 0; mi < 4; mi++) mma_16816(acc[mi], Plo[mi], Phi[mi], Phi[mi], Plo[mi + 1], b0, b1);
#pragma unroll
            for (int s = 0; s < 4; s++) Plo[s] = Plo[s + 1];
#pragma unroll
            for (int s = 0; s < 3; s++) Phi[s] = Phi[s + 1];
            Plo[4] = *reinterpret_cast<const uint32_t*>(kp + 16 * (ki + 5) + 2 * t4 + goff);
            Phi[3] = *reinterpret_cast<const uint32_t*>(kp + 16 * (ki + 4) + 8 + 2 * t4 + goff);
        }
#pragma unroll
        for (int mi = 0; mi < 4; mi++) {
#pragma unroll
            for (int k = 0; k < 4; k++) {
                int i = 16 * mi + g + ((k & 2) ? 8 : 0);
                int a = a0 + 2 * t4 + (k & 1);
                int l = a * CB + i;
                float y = bf16r(acc[mi][k] * inv_sc);
                float u = __bfloat162float(g_xn[(size_t)l * D_MODEL + d0 + c]);
                float sv = y + bf16r(u * dsk);
                g_s[(size_t)l * D_MODEL + d0 + c] = __float2bfloat16_rn(sv);
            }
        }
    }
}

constexpr int BM = 128, BK = 64;
template <int NB, int KTOT, int STAGES, int EPI>
__global__ void __launch_bounds__(288) gemm_kernel(const __grid_constant__ CUtensorMap tmA,
                                                   const __grid_constant__ CUtensorMap tmB,
                                                   const __nv_bfloat16* __restrict__ bias,
                                                   const __nv_bfloat16* __restrict__ xin,
                                                   __nv_bfloat16* __restrict__ out) {
    constexpr int BN = 64 * NB;
    constexpr int A_BYTES = BM * BK * 2;
    constexpr int B_BYTES = BK * BN * 2;
    constexpr int STAGE_BYTES = A_BYTES + B_BYTES;
    constexpr int NKB = KTOT / BK;
    extern __shared__ __align__(1024) unsigned char smraw[];
    __shared__ __align__(8) uint64_t full_bar[STAGES], empty_bar[STAGES];
    uint32_t sbase = (smem_u32(smraw) + 1023) & ~1023u;
    const int warp = threadIdx.x >> 5, lane = threadIdx.x & 31;
    const int m0 = blockIdx.y * BM, n0 = blockIdx.x * BN;

    if (threadIdx.x == 0) {
        for (int s = 0; s < STAGES; s++) {
            mbar_init(smem_u32(&full_bar[s]), 1);
            mbar_init(smem_u32(&empty_bar[s]), 2);
        }
        asm volatile("fence.mbarrier_init.release.cluster;" ::: "memory");
    }
    __syncthreads();

    if (warp == 8) {
        if (lane == 0) {
            for (int kb = 0; kb < NKB; kb++) {
                int s = kb % STAGES;
                uint32_t ph = (kb / STAGES) & 1;
                mbar_wait(smem_u32(&empty_bar[s]), ph ^ 1);
                uint32_t fb = smem_u32(&full_bar[s]);
                mbar_expect_tx(fb, STAGE_BYTES);
                uint32_t sa = sbase + s * STAGE_BYTES;
                uint32_t sb = sa + A_BYTES;
                tma_load_2d(sa, &tmA, fb, kb * BK, m0);
#pragma unroll
                for (int j = 0; j < NB; j++) tma_load_2d(sb + j * (BK * 128), &tmB, fb, n0 + j * 64, kb * BK);
            }
        }
    } else {
        const int wg = warp >> 2;
        float acc[NB][32];
#pragma unroll
        for (int j = 0; j < NB; j++)
#pragma unroll
            for (int i = 0; i < 32; i++) acc[j][i] = 0.f;
        for (int kb = 0; kb < NKB; kb++) {
            int s = kb % STAGES;
            uint32_t ph = (kb / STAGES) & 1;
            mbar_wait(smem_u32(&full_bar[s]), ph);
            uint32_t sa = sbase + s * STAGE_BYTES + wg * (64 * 128);
            uint32_t sb = sbase + s * STAGE_BYTES + A_BYTES;
            wgmma_fence();
#pragma unroll
            for (int kk = 0; kk < 4; kk++) {
                uint64_t da = make_desc(sa + kk * 32, 16, 1024);
#pragma unroll
                for (int j = 0; j < NB; j++) {
                    uint64_t db = make_desc(sb + j * (BK * 128) + kk * 2048, BK * 128, 1024);
                    wgmma_m64n64k16(acc[j], da, db);
                }
            }
            wgmma_commit();
            wgmma_wait<0>();
            if ((threadIdx.x & 127) == 0) mbar_arrive(smem_u32(&empty_bar[s]));
        }
        const int wq = warp & 3;
        const int g = lane >> 2, t4 = lane & 3;
        const int row0 = m0 + wg * 64 + wq * 16 + g;
#pragma unroll
        for (int j = 0; j < NB; j++) {
#pragma unroll
            for (int nb = 0; nb < 8; nb++) {
                int col = n0 + j * 64 + nb * 8 + 2 * t4;
                float b0 = __bfloat162float(bias[col]), b1 = __bfloat162float(bias[col + 1]);
#pragma unroll
                for (int hh = 0; hh < 2; hh++) {
                    int row = row0 + hh * 8;
                    float v0 = bf16r(bf16r(acc[j][nb * 4 + hh * 2]) + b0);
                    float v1 = bf16r(bf16r(acc[j][nb * 4 + hh * 2 + 1]) + b1);
                    if (EPI == 0) {
                        v0 = v0 > 0.f ? v0 : 0.f;
                        v1 = v1 > 0.f ? v1 : 0.f;
                        __nv_bfloat162 o = __floats2bfloat162_rn(v0 * v0, v1 * v1);
                        *reinterpret_cast<__nv_bfloat162*>(out + (size_t)row * F_HID + col) = o;
                    } else {
                        float g0 = bf16r(v0 / (1.0f + __expf(-v0)));
                        float g1 = bf16r(v1 / (1.0f + __expf(-v1)));
                        __nv_bfloat162 sv = *reinterpret_cast<const __nv_bfloat162*>(g_s + (size_t)row * D_MODEL + col);
                        __nv_bfloat162 xv = *reinterpret_cast<const __nv_bfloat162*>(xin + (size_t)row * D_MODEL + col);
                        float2 sf = __bfloat1622float2(sv), xf = __bfloat1622float2(xv);
                        __nv_bfloat162 o = __floats2bfloat162_rn(xf.x + bf16r(sf.x * g0), xf.y + bf16r(sf.y * g1));
                        *reinterpret_cast<__nv_bfloat162*>(out + (size_t)row * D_MODEL + col) = o;
                    }
                }
            }
        }
    }
}

typedef CUresult (*PFN_encodeTiled)(CUtensorMap*, CUtensorMapDataType, cuuint32_t, void*, const cuuint64_t*,
                                    const cuuint64_t*, const cuuint32_t*, const cuuint32_t*, CUtensorMapInterleave,
                                    CUtensorMapSwizzle, CUtensorMapL2promotion, CUtensorMapFloatOOBfill);

static void make_map(PFN_encodeTiled enc, CUtensorMap* tm, void* ptr, uint64_t inner, uint64_t outer, uint32_t box_in,
                     uint32_t box_out) {
    cuuint64_t dims[2] = {inner, outer};
    cuuint64_t strides[1] = {inner * 2};
    cuuint32_t box[2] = {box_in, box_out};
    cuuint32_t es[2] = {1, 1};
    enc(tm, CU_TENSOR_MAP_DATA_TYPE_BFLOAT16, 2, ptr, dims, strides, box, es, CU_TENSOR_MAP_INTERLEAVE_NONE,
        CU_TENSOR_MAP_SWIZZLE_128B, CU_TENSOR_MAP_L2_PROMOTION_L2_256B, CU_TENSOR_MAP_FLOAT_OOB_FILL_NONE);
}

extern "C" void kernel_launch(void* const* d_in, const int* in_sizes, int n_in, void* d_out, int out_size) {
    const __nv_bfloat16* u = (const __nv_bfloat16*)d_in[0];
    const __nv_bfloat16* logAr = (const __nv_bfloat16*)d_in[1];
    const __nv_bfloat16* Aim = (const __nv_bfloat16*)d_in[2];
    const __nv_bfloat16* Cre = (const __nv_bfloat16*)d_in[3];
    const __nv_bfloat16* Cim = (const __nv_bfloat16*)d_in[4];
    const __nv_bfloat16* logdt = (const __nv_bfloat16*)d_in[5];
    const __nv_bfloat16* Dskip = (const __nv_bfloat16*)d_in[6];
    const __nv_bfloat16* w1 = (const __nv_bfloat16*)d_in[8];
    const __nv_bfloat16* b1 = (const __nv_bfloat16*)d_in[9];
    const __nv_bfloat16* w2 = (const __nv_bfloat16*)d_in[10];
    const __nv_bfloat16* b2 = (const __nv_bfloat16*)d_in[11];
    __nv_bfloat16* out = (__nv_bfloat16*)d_out;

    static PFN_encodeTiled enc = nullptr;
    static void *p_xn = nullptr, *p_h = nullptr;
    if (!enc) {
        void* fn = nullptr;
        cudaDriverEntryPointQueryResult st;
        cudaGetDriverEntryPoint("cuTensorMapEncodeTiled", &fn, cudaEnableDefault, &st);
        enc = (PFN_encodeTiled)fn;
        cudaGetSymbolAddress(&p_xn, g_xn);
        cudaGetSymbolAddress(&p_h, g_h);
    }
    CUtensorMap tmA1, tmB1, tmA2, tmB2;
    make_map(enc, &tmA1, p_xn, D_MODEL, L_SEQ, 64, 128);
    make_map(enc, &tmB1, (void*)w1, F_HID, D_MODEL, 64, 64);
    make_map(enc, &tmA2, p_h, F_HID, L_SEQ, 64, 128);
    make_map(enc, &tmB2, (void*)w2, D_MODEL, F_HID, 64, 64);

    cudaStream_t st = cudaStreamPerThread;

    ln_kernel<<<L_SEQ / 8, 256, 0, st>>>(u);

    const int kg_smem = (17 + 16) * 128 * sizeof(float2);
    cudaFuncSetAttribute(kgen_kernel, cudaFuncAttributeMaxDynamicSharedMemorySize, kg_smem);
    kgen_kernel<<<D_MODEL, 128, kg_smem, st>>>(logAr, Aim, Cre, Cim, logdt);

    const int cv_smem = sizeof(ConvSmem);
    cudaFuncSetAttribute(conv_kernel, cudaFuncAttributeMaxDynamicSharedMemorySize, cv_smem);
    conv_kernel<<<D_MODEL / CONV_CH, 256, cv_smem, st>>>(Dskip);

    {
        constexpr int NB = 4, ST = 4;
        const int smem = ST * (BM * BK * 2 + BK * 64 * NB * 2) + 1024;
        auto k = gemm_kernel<NB, D_MODEL, ST, 0>;
        cudaFuncSetAttribute(k, cudaFuncAttributeMaxDynamicSharedMemorySize, smem);
        k<<<dim3(F_HID / (64 * NB), L_SEQ / BM), 288, smem, st>>>(tmA1, tmB1, b1, nullptr, (__nv_bfloat16*)p_h);
    }
    {
        constexpr int NB = 1, ST = 6;
        const int smem = ST * (BM * BK * 2 + BK * 64 * NB * 2) + 1024;
        auto k = gemm_kernel<NB, F_HID, ST, 1>;
        cudaFuncSetAttribute(k, cudaFuncAttributeMaxDynamicSharedMemorySize, smem);
        k<<<dim3(D_MODEL / (64 * NB), L_SEQ / BM), 288, smem, st>>>(tmA2, tmB2, b2, u, out);
    }
}
```

```cpp
#include <cuda_runtime.h>
#include <cuda_bf16.h>
#include <cuda_fp16.h>
#include <cuda.h>
#include <stdint.h>

constexpr int L_SEQ = 2048;
constexpr int D_MODEL = 512;
constexpr int N_STATE = 128;
constexpr int F_HID = 1792;

__device__ __align__(1024) __nv_bfloat16 g_xn[L_SEQ * D_MODEL];
__device__ __align__(1024) __nv_bfloat16 g_h[L_SEQ * F_HID];
__device__ __align__(1024) __nv_bfloat16 g_s[L_SEQ * D_MODEL];

__device__ __forceinline__ float bf16r(float x) { return __bfloat162float(__float2bfloat16_rn(x)); }

__device__ __forceinline__ uint32_t smem_u32(const void* p) {
    return (uint32_t)__cvta_generic_to_shared(p);
}
__device__ __forceinline__ void mbar_init(uint32_t bar, uint32_t count) {
    asm volatile("mbarrier.init.shared::cta.b64 [%0], %1;" ::"r"(bar), "r"(count));
}
__device__ __forceinline__ void mbar_expect_tx(uint32_t bar, uint32_t bytes) {
    asm volatile("mbarrier.arrive.expect_tx.shared::cta.b64 _, [%0], %1;" ::"r"(bar), "r"(bytes) : "memory");
}
__device__ __forceinline__ void mbar_arrive(uint32_t bar) {
    asm volatile("mbarrier.arrive.shared::cta.b64 _, [%0];" ::"r"(bar) : "memory");
}
__device__ __forceinline__ bool mbar_try_wait(uint32_t bar, uint32_t parity) {
    uint32_t ok;
    asm volatile(
        "{\n"
        ".reg .pred p;\n"
        "mbarrier.try_wait.parity.shared::cta.b64 p, [%1], %2;\n"
        "selp.u32 %0, 1, 0, p;\n"
        "}\n" : "=r"(ok) : "r"(bar), "r"(parity) : "memory");
    return ok != 0;
}
__device__ __forceinline__ void mbar_wait(uint32_t bar, uint32_t parity) {
    if (mbar_try_wait(bar, parity)) return;
    for (int it = 0; it < (1 << 24); it++) {
        if (mbar_try_wait(bar, parity)) return;
    }
    __trap();
}
__device__ __forceinline__ void tma_load_2d(uint32_t smem_dst, const CUtensorMap* tm, uint32_t bar, int c0, int c1) {
    asm volatile(
        "cp.async.bulk.tensor.2d.shared::cluster.global.mbarrier::complete_tx::bytes [%0], [%1, {%3, %4}], [%2];"
        ::"r"(smem_dst), "l"((uint64_t)tm), "r"(bar), "r"(c0), "r"(c1) : "memory");
}
__device__ __forceinline__ void wgmma_fence() { asm volatile("wgmma.fence.sync.aligned;" ::: "memory"); }
__device__ __forceinline__ void wgmma_commit() { asm volatile("wgmma.commit_group.sync.aligned;" ::: "memory"); }
template <int N>
__device__ __forceinline__ void wgmma_wait() { asm volatile("wgmma.wait_group.sync.aligned %0;" ::"n"(N) : "memory"); }

__device__ __forceinline__ uint64_t make_desc(uint32_t saddr, uint32_t lbo_bytes, uint32_t sbo_bytes) {
    uint64_t d = 0;
    d |= (uint64_t)((saddr & 0x3FFFF) >> 4);
    d |= (uint64_t)((lbo_bytes & 0x3FFFF) >> 4) << 16;
    d |= (uint64_t)((sbo_bytes & 0x3FFFF) >> 4) << 32;
    d |= (uint64_t)1 << 62;
    return d;
}

__device__ __forceinline__ void wgmma_m64n64k16(float (&d)[32], uint64_t da, uint64_t db) {
    asm volatile(
        "{\n"
        ".reg .pred p;\n"
        "setp.ne.b32 p, %34, 0;\n"
        "wgmma.mma_async.sync.aligned.m64n64k16.f32.bf16.bf16 "
        "{%0,%1,%2,%3,%4,%5,%6,%7,%8,%9,%10,%11,%12,%13,%14,%15,"
        "%16,%17,%18,%19,%20,%21,%22,%23,%24,%25,%26,%27,%28,%29,%30,%31},"
        " %32, %33, p, 1, 1, 0, 1;\n"
        "}\n"
        : "+f"(d[0]), "+f"(d[1]), "+f"(d[2]), "+f"(d[3]), "+f"(d[4]), "+f"(d[5]), "+f"(d[6]), "+f"(d[7]),
          "+f"(d[8]), "+f"(d[9]), "+f"(d[10]), "+f"(d[11]), "+f"(d[12]), "+f"(d[13]), "+f"(d[14]), "+f"(d[15]),
          "+f"(d[16]), "+f"(d[17]), "+f"(d[18]), "+f"(d[19]), "+f"(d[20]), "+f"(d[21]), "+f"(d[22]), "+f"(d[23]),
          "+f"(d[24]), "+f"(d[25]), "+f"(d[26]), "+f"(d[27]), "+f"(d[28]), "+f"(d[29]), "+f"(d[30]), "+f"(d[31])
        : "l"(da), "l"(db), "r"(1));
}

__global__ void __launch_bounds__(256) ln_kernel(const __nv_bfloat16* __restrict__ x) {
    int warp = (blockIdx.x * blockDim.x + threadIdx.x) >> 5;
    int lane = threadIdx.x & 31;
    if (warp >= L_SEQ) return;
    const uint4* xr = reinterpret_cast<const uint4*>(x + (size_t)warp * D_MODEL);
    float v[16];
#pragma unroll
    for (int i = 0; i < 2; i++) {
        uint4 t = xr[lane + 32 * i];
        const __nv_bfloat162* p = reinterpret_cast<const __nv_bfloat162*>(&t);
#pragma unroll
        for (int j = 0; j < 4; j++) {
            float2 f = __bfloat1622float2(p[j]);
            v[i * 8 + 2 * j] = f.x;
            v[i * 8 + 2 * j + 1] = f.y;
        }
    }
    float s = 0.f;
#pragma unroll
    for (int i = 0; i < 16; i++) s += v[i];
#pragma unroll
    for (int o = 16; o > 0; o >>= 1) s += __shfl_xor_sync(0xffffffffu, s, o);
    float mean = s * (1.0f / D_MODEL);
    float q = 0.f;
#pragma unroll
    for (int i = 0; i < 16; i++) { float d = v[i] - mean; q += d * d; }
#pragma unroll
    for (int o = 16; o > 0; o >>= 1) q += __shfl_xor_sync(0xffffffffu, q, o);
    float var = bf16r(q * (1.0f / D_MODEL));
    float mb = bf16r(mean);
    float sd = bf16r(sqrtf(bf16r(var + 1e-5f)));
    uint4* outr = reinterpret_cast<uint4*>(g_xn + (size_t)warp * D_MODEL);
#pragma unroll
    for (int i = 0; i < 2; i++) {
        uint4 t;
        __nv_bfloat162* p = reinterpret_cast<__nv_bfloat162*>(&t);
#pragma unroll
        for (int j = 0; j < 4; j++) {
            float a = bf16r(v[i * 8 + 2 * j] - mb) / sd;
            float b = bf16r(v[i * 8 + 2 * j + 1] - mb) / sd;
            p[j] = __floats2bfloat162_rn(a, b);
        }
        outr[lane + 32 * i] = t;
    }
}

constexpr int CB = 64;
constexpr int CONV_CH = 4;
constexpr int KP_LEN = L_SEQ + CB + 32;
constexpr int UR_BLK = 72;
constexpr int UR_NBLK = (L_SEQ + 512) / CB;
constexpr int TROW = 264;
constexpr int TROWS = 32;
struct ConvArrays {
    __half kpE[CONV_CH][KP_LEN];
    __half kpO[CONV_CH][KP_LEN + 32];
    __half ur[CONV_CH][UR_NBLK * UR_BLK];
};
struct ConvTables {
    __half t[CONV_CH][TROWS * TROW];
};
struct ConvSmem {
    union {
        ConvArrays a;
        ConvTables t;
    } u;
    float kd[CONV_CH][2][648];
    __nv_bfloat16 ustage[L_SEQ][CONV_CH];
    float red[CONV_CH][4];
};

__device__ __forceinline__ void mma_16816(float (&c)[4], uint32_t a0, uint32_t a1, uint32_t a2, uint32_t a3,
                                          uint32_t b0, uint32_t b1) {
    asm volatile(
        "mma.sync.aligned.m16n8k16.row.col.f32.f16.f16.f32 {%0,%1,%2,%3}, {%4,%5,%6,%7}, {%8,%9}, {%0,%1,%2,%3};"
        : "+f"(c[0]), "+f"(c[1]), "+f"(c[2]), "+f"(c[3])
        : "r"(a0), "r"(a1), "r"(a2), "r"(a3), "r"(b0), "r"(b1));
}
__device__ __forceinline__ void ldsm_x4(uint32_t addr, uint32_t& r0, uint32_t& r1, uint32_t& r2, uint32_t& r3) {
    asm volatile("ldmatrix.sync.aligned.m8n8.x4.shared.b16 {%0,%1,%2,%3}, [%4];"
                 : "=r"(r0), "=r"(r1), "=r"(r2), "=r"(r3) : "r"(addr));
}
__device__ __forceinline__ void ldsm_x2(uint32_t addr, uint32_t& r0, uint32_t& r1) {
    asm volatile("ldmatrix.sync.aligned.m8n8.x2.shared.b16 {%0,%1}, [%2];" : "=r"(r0), "=r"(r1) : "r"(addr));
}
__device__ __forceinline__ void bar_sync(int id, int n) { asm volatile("bar.sync %0, %1;" ::"r"(id), "r"(n) : "memory"); }

__device__ __forceinline__ float2 cexp_fast(float re, float im) {
    float e = __expf(re);
    float t = im * 0.15915494309189535f;
    t -= rintf(t);
    float ang = t * 6.283185307179586f;
    return make_float2(e * __cosf(ang), e * __sinf(ang));
}
__device__ __forceinline__ float2 cmul(float2 a, float2 b) {
    return make_float2(a.x * b.x - a.y * b.y, a.x * b.y + a.y * b.x);
}

__global__ void __launch_bounds__(256) conv_kernel(const __nv_bfloat16* __restrict__ logAr,
                                                   const __nv_bfloat16* __restrict__ Aim,
                                                   const __nv_bfloat16* __restrict__ Cre,
                                                   const __nv_bfloat16* __restrict__ Cim,
                                                   const __nv_bfloat16* __restrict__ logdt,
                                                   const __nv_bfloat16* __restrict__ Dskip) {
    extern __shared__ __align__(128) unsigned char smraw[];
    ConvSmem& S = *reinterpret_cast<ConvSmem*>(smraw);
    const int d0 = blockIdx.x * CONV_CH;
    const int tid = threadIdx.x, warp = tid >> 5, lane = tid & 31;
    const int c = warp >> 1;
    const int sub = warp & 1;
    const int t64 = tid & 63;
    const int g = lane >> 2, t4 = lane & 3;

#pragma unroll
    for (int i = 0; i < L_SEQ / 256; i++) {
        int l = tid + 256 * i;
        asm volatile("cp.async.ca.shared.global [%0], [%1], 8;" ::"r"(smem_u32(&S.ustage[l][0])),
                     "l"(g_xn + (size_t)l * D_MODEL + d0) : "memory");
    }
    asm volatile("cp.async.commit_group;" ::: "memory");

    const int d = d0 + c;
    const float dt = bf16r(expf(__bfloat162float(logdt[d])));
    float are[2], aim[2];
    float2 Cc[2];
    float mx = 0.f;
#pragma unroll
    for (int q = 0; q < 2; q++) {
        int n = t64 + 64 * q;
        float ar = -bf16r(expf(__bfloat162float(logAr[d * N_STATE + n])));
        float ai = __bfloat162float(Aim[d * N_STATE + n]);
        are[q] = ar * dt;
        aim[q] = ai * dt;
        Cc[q] = make_float2(__bfloat162float(Cre[d * N_STATE + n]) * dt, __bfloat162float(Cim[d * N_STATE + n]) * dt);
        mx = fmaxf(mx, fmaxf(fabsf(Cc[q].x), fabsf(Cc[q].y)));
    }
#pragma unroll
    for (int o = 16; o > 0; o >>= 1) mx = fmaxf(mx, __shfl_xor_sync(0xffffffffu, mx, o));
    if (lane == 0) S.red[c][sub] = mx;
    bar_sync(1 + c, 64);
    mx = fmaxf(S.red[c][0], S.red[c][1]);
    float scale = 1.0f;
    if (mx > 0.f && mx < 3.0e38f) {
        int e;
        frexpf(mx, &e);
        e = max(-120, min(120, e));
        scale = ldexpf(1.0f, -e);
    }
#pragma unroll
    for (int q = 0; q < 2; q++) { Cc[q].x *= scale; Cc[q].y *= scale; }

    __half* T = &S.u.t.t[c][0];
    float2 zs[2];
#pragma unroll
    for (int q = 0; q < 2; q++) zs[q] = cexp_fast(are[q], aim[q]);
    float k2048 = 0.f;
#pragma unroll 1
    for (int r = 0; r < 4; r++) {
        const int nlo = (r == 0) ? 16 : 8;
        const float pbase = (r == 0) ? 0.f : (float)(128 << r);
        const float pratio = (r == 0) ? 16.f : (float)(8 << r);
#pragma unroll
        for (int q = 0; q < 2; q++) {
            int n = t64 + 64 * q;
            float2 w = (r == 0) ? Cc[q] : cmul(Cc[q], cexp_fast(are[q] * pbase, aim[q] * pbase));
            float2 ratio = cexp_fast(are[q] * pratio, aim[q] * pratio);
#pragma unroll
            for (int hi = 0; hi < 16; hi++) {
                T[hi * TROW + n] = __float2half_rn(w.x);
                T[hi * TROW + 128 + n] = __float2half_rn(-w.y);
                w = cmul(w, ratio);
            }
            if (r == 3) k2048 += w.x;
            float2 z = make_float2(1.f, 0.f);
            for (int lo = 0; lo < nlo; lo++) {
                T[(16 + lo) * TROW + n] = __float2half_rn(z.x);
                T[(16 + lo) * TROW + 128 + n] = __float2half_rn(z.y);
                z = cmul(z, zs[q]);
            }
            zs[q] = cmul(zs[q], zs[q]);
        }
        bar_sync(1 + c, 64);
        float acc[2][4];
#pragma unroll
        for (int i = 0; i < 2; i++)
#pragma unroll
            for (int k = 0; k < 4; k++) acc[i][k] = 0.f;
        {
            uint32_t abase = smem_u32(T) + (uint32_t)(((lane & 7) + ((lane >> 3) & 1) * 8) * TROW + (lane >> 4) * 8) * 2;
            uint32_t bbase = smem_u32(T) + (uint32_t)((16 + (lane & 7) + (lane >> 4) * 8) * TROW + ((lane >> 3) & 1) * 8) * 2;
#pragma unroll
            for (int kt = 0; kt < 8; kt++) {
                int k0 = (8 * sub + kt) * 16;
                uint32_t a0, a1, a2, a3, b0, b1, b2, b3;
                ldsm_x4(abase + k0 * 2, a0, a1, a2, a3);
                if (r == 0) {
                    ldsm_x4(bbase + k0 * 2, b0, b1, b2, b3);
                    mma_16816(acc[0], a0, a1, a2, a3, b0, b1);
                    mma_16816(acc[1], a0, a1, a2, a3, b2, b3);
                } else {
                    ldsm_x2(bbase + k0 * 2, b0, b1);
                    mma_16816(acc[0], a0, a1, a2, a3, b0, b1);
                }
            }
        }
        {
            const int obase = (r == 0) ? 0 : (256 + (r - 1) * 128);
            float* kd = &S.kd[c][sub][0];
            kd[obase + g * nlo + 2 * t4] = acc[0][0];
            kd[obase + g * nlo + 2 * t4 + 1] = acc[0][1];
            kd[obase + (g + 8) * nlo + 2 * t4] = acc[0][2];
            kd[obase + (g + 8) * nlo + 2 * t4 + 1] = acc[0][3];
            if (r == 0) {
                kd[g * 16 + 8 + 2 * t4] = acc[1][0];
                kd[g * 16 + 8 + 2 * t4 + 1] = acc[1][1];
                kd[(g + 8) * 16 + 8 + 2 * t4] = acc[1][2];
                kd[(g + 8) * 16 + 8 + 2 * t4 + 1] = acc[1][3];
            }
        }
        bar_sync(1 + c, 64);
    }
#pragma unroll
    for (int o = 16; o > 0; o >>= 1) k2048 += __shfl_xor_sync(0xffffffffu, k2048, o);
    if (lane == 0) S.kd[c][sub][640] = k2048;
    asm volatile("cp.async.wait_group 0;" ::: "memory");
    __syncthreads();

    {
        const float* k0p = &S.kd[c][0][0];
        const float* k1p = &S.kd[c][1][0];
        for (int t = 2 * t64; t < KP_LEN; t += 128) {
            float v[3];
#pragma unroll
            for (int e = 0; e < 3; e++) {
                int j = t + e - (CB - 1);
                float val = 0.f;
                if (j >= 0 && j < L_SEQ) {
                    int p = (int)__bfloat162float(__float2bfloat16_rn((float)j));
                    int idx;
                    if (p < 256) idx = p;
                    else if (p < 512) idx = 256 + ((p - 256) >> 1);
                    else if (p < 1024) idx = 384 + ((p - 512) >> 2);
                    else idx = 512 + ((p - 1024) >> 3);
                    val = 2.0f * (k0p[idx] + k1p[idx]);
                }
                v[e] = val;
            }
            *reinterpret_cast<__half2*>(&S.u.a.kpE[c][t]) = __floats2half2_rn(v[0], v[1]);
            *reinterpret_cast<__half2*>(&S.u.a.kpO[c][t]) = __floats2half2_rn(v[1], v[2]);
        }
    }
    for (int r = 2 * t64; r < UR_NBLK * CB; r += 128) {
        int l = L_SEQ - 1 - r;
        int pos = (r / CB) * UR_BLK + (r % CB);
        float v0 = 0.f, v1 = 0.f;
        if (l >= 1) {
            v0 = __bfloat162float(S.ustage[l][c]);
            v1 = __bfloat162float(S.ustage[l - 1][c]);
        }
        *reinterpret_cast<__half2*>(&S.u.a.ur[c][pos]) = __floats2half2_rn(v0, v1);
    }
    bar_sync(1 + c, 64);

    const __half* kp = (g & 1) ? &S.u.a.kpO[c][0] : &S.u.a.kpE[c][0];
    const uint32_t kpa = smem_u32(kp) + (uint32_t)(2 * t4 + (g & ~1)) * 2;
    const float inv_sc = 1.0f / scale;
    const float dsk = __bfloat162float(Dskip[d]);
    const int ntA = sub ? 1 : 0, ntB = sub ? 2 : 3;
    float accA[4][4], accB[4][4];
#pragma unroll
    for (int mi = 0; mi < 4; mi++)
#pragma unroll
        for (int k = 0; k < 4; k++) { accA[mi][k] = 0.f; accB[mi][k] = 0.f; }
    const int lm = lane >> 3, lr = lane & 7;
    const int lnt = (lm < 2) ? ntA : ntB;
    const int rblk0 = (L_SEQ / CB) - (lnt * 8 + lr + 1);
    const uint32_t ubase = smem_u32(&S.u.a.ur[c][0]) + (uint32_t)(rblk0 * UR_BLK + (lm & 1) * 8) * 2;
    const int rblk1 = (L_SEQ / CB) - (ntB * 8 + lr + 1);
    const uint32_t ubaseT = smem_u32(&S.u.a.ur[c][0]) + (uint32_t)(rblk1 * UR_BLK + lm * 8) * 2;

    uint32_t Plo[4], Phi[4];
    auto ldk = [&](int off) -> uint32_t {
        uint32_t v;
        asm volatile("ld.shared.b32 %0, [%1];" : "=r"(v) : "r"(kpa + (uint32_t)off * 2));
        return v;
    };
#pragma unroll
    for (int s = 0; s < 4; s++) { Plo[s] = ldk(16 * s); Phi[s] = ldk(16 * s + 8); }
    const int nkA = 32 * (ntA + 1), nkB = 32 * (ntB + 1);
    int ki = 0;
    for (; ki < nkA; ki += 4) {
        uint32_t ub = ubase + (uint32_t)((ki >> 2) * UR_BLK) * 2;
#pragma unroll
        for (int kq = 0; kq < 4; kq++) {
            uint32_t b0, b1, b2, b3;
            ldsm_x4(ub + kq * 32, b0, b1, b2, b3);
            uint32_t nl = ldk(16 * (ki + kq + 4));
            uint32_t nh = ldk(16 * (ki + kq + 4) + 8);
#pragma unroll
            for (int mi = 0; mi < 4; mi++) {
                uint32_t pl = Plo[(kq + mi) & 3], ph = Phi[(kq + mi) & 3];
                uint32_t pn = (mi < 3) ? Plo[(kq + mi + 1) & 3] : nl;
                mma_16816(accA[mi], pl, ph, ph, pn, b0, b1);
                mma_16816(accB[mi], pl, ph, ph, pn, b2, b3);
            }
            Plo[kq] = nl;
            Phi[kq] = nh;
        }
    }
    for (; ki < nkB; ki += 4) {
        uint32_t ub = ubaseT + (uint32_t)((ki >> 2) * UR_BLK) * 2;
        uint32_t b[8];
        ldsm_x4(ub, b[0], b[1], b[2], b[3]);
        ldsm_x4(ub + 64, b[4], b[5], b[6], b[7]);
#pragma unroll
        for (int kq = 0; kq < 4; kq++) {
            uint32_t nl = ldk(16 * (ki + kq + 4));
            uint32_t nh = ldk(16 * (ki + kq + 4) + 8);
#pragma unroll
            for (int mi = 0; mi < 4; mi++) {
                uint32_t pl = Plo[(kq + mi) & 3], ph = Phi[(kq + mi) & 3];
                uint32_t pn = (mi < 3) ? Plo[(kq + mi + 1) & 3] : nl;
                mma_16816(accB[mi], pl, ph, ph, pn, b[2 * kq], b[2 * kq + 1]);
            }
            Plo[kq] = nl;
            Phi[kq] = nh;
        }
    }
#pragma unroll
    for (int mi = 0; mi < 4; mi++) {
#pragma unroll
        for (int k = 0; k < 4; k++) {
            int i = 16 * mi + g + ((k & 2) ? 8 : 0);
            {
                int l = (ntA * 8 + 2 * t4 + (k & 1)) * CB + i;
                float u = __bfloat162float(S.ustage[l][c]);
                S.ustage[l][c] = __float2bfloat16_rn(bf16r(accA[mi][k] * inv_sc) + bf16r(u * dsk));
            }
            {
                int l = (ntB * 8 + 2 * t4 + (k & 1)) * CB + i;
                float u = __bfloat162float(S.ustage[l][c]);
                S.ustage[l][c] = __float2bfloat16_rn(bf16r(accB[mi][k] * inv_sc) + bf16r(u * dsk));
            }
        }
    }
    __syncthreads();
#pragma unroll
    for (int i = 0; i < L_SEQ / 256; i++) {
        int l = tid + 256 * i;
        *reinterpret_cast<uint2*>(g_s + (size_t)l * D_MODEL + d0) = *reinterpret_cast<const uint2*>(&S.ustage[l][0]);
    }
}

constexpr int BM = 128, BK = 64;
template <int NB, int KTOT, int STAGES, int EPI>
__global__ void __launch_bounds__(288) gemm_kernel(const __grid_constant__ CUtensorMap tmA,
                                                   const __grid_constant__ CUtensorMap tmB,
                                                   const __nv_bfloat16* __restrict__ bias,
                                                   const __nv_bfloat16* __restrict__ xin,
                                                   __nv_bfloat16* __restrict__ out) {
    constexpr int BN = 64 * NB;
    constexpr int A_BYTES = BM * BK * 2;
    constexpr int B_BYTES = BK * BN * 2;
    constexpr int STAGE_BYTES = A_BYTES + B_BYTES;
    constexpr int NKB = KTOT / BK;
    extern __shared__ __align__(1024) unsigned char smraw[];
    __shared__ __align__(8) uint64_t full_bar[STAGES], empty_bar[STAGES];
    uint32_t sbase = (smem_u32(smraw) + 1023) & ~1023u;
    const int warp = threadIdx.x >> 5, lane = threadIdx.x & 31;
    const int m0 = blockIdx.y * BM, n0 = blockIdx.x * BN;

    if (threadIdx.x == 0) {
        for (int s = 0; s < STAGES; s++) {
            mbar_init(smem_u32(&full_bar[s]), 1);
            mbar_init(smem_u32(&empty_bar[s]), 2);
        }
        asm volatile("fence.mbarrier_init.release.cluster;" ::: "memory");
    }
    __syncthreads();

    if (warp == 8) {
        if (lane == 0) {
            for (int kb = 0; kb < NKB; kb++) {
                int s = kb % STAGES;
                uint32_t ph = (kb / STAGES) & 1;
                mbar_wait(smem_u32(&empty_bar[s]), ph ^ 1);
                uint32_t fb = smem_u32(&full_bar[s]);
                mbar_expect_tx(fb, STAGE_BYTES);
                uint32_t sa = sbase + s * STAGE_BYTES;
                uint32_t sb = sa + A_BYTES;
                tma_load_2d(sa, &tmA, fb, kb * BK, m0);
#pragma unroll
                for (int j = 0; j < NB; j++) tma_load_2d(sb + j * (BK * 128), &tmB, fb, n0 + j * 64, kb * BK);
            }
        }
    } else {
        const int wg = warp >> 2;
        float acc[NB][32];
#pragma unroll
        for (int j = 0; j < NB; j++)
#pragma unroll
            for (int i = 0; i < 32; i++) acc[j][i] = 0.f;
        for (int kb = 0; kb < NKB; kb++) {
            int s = kb % STAGES;
            uint32_t ph = (kb / STAGES) & 1;
            mbar_wait(smem_u32(&full_bar[s]), ph);
            uint32_t sa = sbase + s * STAGE_BYTES + wg * (64 * 128);
            uint32_t sb = sbase + s * STAGE_BYTES + A_BYTES;
            wgmma_fence();
#pragma unroll
            for (int kk = 0; kk < 4; kk++) {
                uint64_t da = make_desc(sa + kk * 32, 16, 1024);
#pragma unroll
                for (int j = 0; j < NB; j++) {
                    uint64_t db = make_desc(sb + j * (BK * 128) + kk * 2048, BK * 128, 1024);
                    wgmma_m64n64k16(acc[j], da, db);
                }
            }
            wgmma_commit();
            wgmma_wait<0>();
            if ((threadIdx.x & 127) == 0) mbar_arrive(smem_u32(&empty_bar[s]));
        }
        const int wq = warp & 3;
        const int g = lane >> 2, t4 = lane & 3;
        const int row0 = m0 + wg * 64 + wq * 16 + g;
#pragma unroll
        for (int j = 0; j < NB; j++) {
#pragma unroll
            for (int nb = 0; nb < 8; nb++) {
                int col = n0 + j * 64 + nb * 8 + 2 * t4;
                float b0 = __bfloat162float(bias[col]), b1 = __bfloat162float(bias[col + 1]);
#pragma unroll
                for (int hh = 0; hh < 2; hh++) {
                    int row = row0 + hh * 8;
                    float v0 = bf16r(bf16r(acc[j][nb * 4 + hh * 2]) + b0);
                    float v1 = bf16r(bf16r(acc[j][nb * 4 + hh * 2 + 1]) + b1);
                    if (EPI == 0) {
                        v0 = v0 > 0.f ? v0 : 0.f;
                        v1 = v1 > 0.f ? v1 : 0.f;
                        __nv_bfloat162 o = __floats2bfloat162_rn(v0 * v0, v1 * v1);
                        *reinterpret_cast<__nv_bfloat162*>(out + (size_t)row * F_HID + col) = o;
                    } else {
                        float g0 = bf16r(v0 / (1.0f + __expf(-v0)));
                        float g1 = bf16r(v1 / (1.0f + __expf(-v1)));
                        __nv_bfloat162 sv = *reinterpret_cast<const __nv_bfloat162*>(g_s + (size_t)row * D_MODEL + col);
                        __nv_bfloat162 xv = *reinterpret_cast<const __nv_bfloat162*>(xin + (size_t)row * D_MODEL + col);
                        float2 sf = __bfloat1622float2(sv), xf = __bfloat1622float2(xv);
                        __nv_bfloat162 o = __floats2bfloat162_rn(xf.x + bf16r(sf.x * g0), xf.y + bf16r(sf.y * g1));
                        *reinterpret_cast<__nv_bfloat162*>(out + (size_t)row * D_MODEL + col) = o;
                    }
                }
            }
        }
    }
}

typedef CUresult (*PFN_encodeTiled)(CUtensorMap*, CUtensorMapDataType, cuuint32_t, void*, const cuuint64_t*,
                                    const cuuint64_t*, const cuuint32_t*, const cuuint32_t*, CUtensorMapInterleave,
                                    CUtensorMapSwizzle, CUtensorMapL2promotion, CUtensorMapFloatOOBfill);

static void make_map(PFN_encodeTiled enc, CUtensorMap* tm, void* ptr, uint64_t inner, uint64_t outer, uint32_t box_in,
                     uint32_t box_out) {
    cuuint64_t dims[2] = {inner, outer};
    cuuint64_t strides[1] = {inner * 2};
    cuuint32_t box[2] = {box_in, box_out};
    cuuint32_t es[2] = {1, 1};
    enc(tm, CU_TENSOR_MAP_DATA_TYPE_BFLOAT16, 2, ptr, dims, strides, box, es, CU_TENSOR_MAP_INTERLEAVE_NONE,
        CU_TENSOR_MAP_SWIZZLE_128B, CU_TENSOR_MAP_L2_PROMOTION_L2_256B, CU_TENSOR_MAP_FLOAT_OOB_FILL_NONE);
}

extern "C" void kernel_launch(void* const* d_in, const int* in_sizes, int n_in, void* d_out, int out_size) {
    const __nv_bfloat16* u = (const __nv_bfloat16*)d_in[0];
    const __nv_bfloat16* logAr = (const __nv_bfloat16*)d_in[1];
    const __nv_bfloat16* Aim = (const __nv_bfloat16*)d_in[2];
    const __nv_bfloat16* Cre = (const __nv_bfloat16*)d_in[3];
    const __nv_bfloat16* Cim = (const __nv_bfloat16*)d_in[4];
    const __nv_bfloat16* logdt = (const __nv_bfloat16*)d_in[5];
    const __nv_bfloat16* Dskip = (const __nv_bfloat16*)d_in[6];
    const __nv_bfloat16* w1 = (const __nv_bfloat16*)d_in[8];
    const __nv_bfloat16* b1 = (const __nv_bfloat16*)d_in[9];
    const __nv_bfloat16* w2 = (const __nv_bfloat16*)d_in[10];
    const __nv_bfloat16* b2 = (const __nv_bfloat16*)d_in[11];
    __nv_bfloat16* out = (__nv_bfloat16*)d_out;

    static PFN_encodeTiled enc = nullptr;
    static void *p_xn = nullptr, *p_h = nullptr;
    if (!enc) {
        void* fn = nullptr;
        cudaDriverEntryPointQueryResult st;
        cudaGetDriverEntryPoint("cuTensorMapEncodeTiled", &fn, cudaEnableDefault, &st);
        enc = (PFN_encodeTiled)fn;
        cudaGetSymbolAddress(&p_xn, g_xn);
        cudaGetSymbolAddress(&p_h, g_h);
    }
    CUtensorMap tmA1, tmB1, tmA2, tmB2;
    make_map(enc, &tmA1, p_xn, D_MODEL, L_SEQ, 64, 128);
    make_map(enc, &tmB1, (void*)w1, F_HID, D_MODEL, 64, 64);
    make_map(enc, &tmA2, p_h, F_HID, L_SEQ, 64, 128);
    make_map(enc, &tmB2, (void*)w2, D_MODEL, F_HID, 64, 64);

    cudaStream_t st = cudaStreamPerThread;

    ln_kernel<<<L_SEQ / 8, 256, 0, st>>>(u);

    const int cv_smem = sizeof(ConvSmem);
    cudaFuncSetAttribute(conv_kernel, cudaFuncAttributeMaxDynamicSharedMemorySize, cv_smem);
    conv_kernel<<<D_MODEL / CONV_CH, 256, cv_smem, st>>>(logAr, Aim, Cre, Cim, logdt, Dskip);

    {
        constexpr int NB = 4, ST = 4;
        const int smem = ST * (BM * BK * 2 + BK * 64 * NB * 2) + 1024;
        auto k = gemm_kernel<NB, D_MODEL, ST, 0>;
        cudaFuncSetAttribute(k, cudaFuncAttributeMaxDynamicSharedMemorySize, smem);
        k<<<dim3(F_HID / (64 * NB), L_SEQ / BM), 288, smem, st>>>(tmA1, tmB1, b1, nullptr, (__nv_bfloat16*)p_h);
    }
    {
        constexpr int NB = 1, ST = 6;
        const int smem = ST * (BM * BK * 2 + BK * 64 * NB * 2) + 1024;
        auto k = gemm_kernel<NB, F_HID, ST, 1>;
        cudaFuncSetAttribute(k, cudaFuncAttributeMaxDynamicSharedMemorySize, smem);
        k<<<dim3(D_MODEL / (64 * NB), L_SEQ / BM), 288, smem, st>>>(tmA2, tmB2, b2, u, out);
    }
}
```

```cpp
#include <cuda_runtime.h>
#include <cuda_bf16.h>
#include <cuda_fp16.h>
#include <cuda.h>
#include <stdint.h>

constexpr int L_SEQ = 2048;
constexpr int D_MODEL = 512;
constexpr int N_STATE = 128;
constexpr int F_HID = 1792;

__device__ __align__(1024) __nv_bfloat16 g_xn[L_SEQ * D_MODEL];
__device__ __align__(1024) __nv_bfloat16 g_h[L_SEQ * F_HID];
__device__ __align__(1024) __nv_bfloat16 g_s[L_SEQ * D_MODEL];

#define TS(k, slot) do {} while (0)
__device__ __forceinline__ float bf16r(float x) { return __bfloat162float(__float2bfloat16_rn(x)); }

__device__ __forceinline__ uint32_t smem_u32(const void* p) {
    return (uint32_t)__cvta_generic_to_shared(p);
}
__device__ __forceinline__ void mbar_init(uint32_t bar, uint32_t count) {
    asm volatile("mbarrier.init.shared::cta.b64 [%0], %1;" ::"r"(bar), "r"(count));
}
__device__ __forceinline__ void mbar_expect_tx(uint32_t bar, uint32_t bytes) {
    asm volatile("mbarrier.arrive.expect_tx.shared::cta.b64 _, [%0], %1;" ::"r"(bar), "r"(bytes) : "memory");
}
__device__ __forceinline__ void mbar_arrive(uint32_t bar) {
    asm volatile("mbarrier.arrive.shared::cta.b64 _, [%0];" ::"r"(bar) : "memory");
}
__device__ __forceinline__ bool mbar_try_wait(uint32_t bar, uint32_t parity) {
    uint32_t ok;
    asm volatile(
        "{\n"
        ".reg .pred p;\n"
        "mbarrier.try_wait.parity.shared::cta.b64 p, [%1], %2;\n"
        "selp.u32 %0, 1, 0, p;\n"
        "}\n" : "=r"(ok) : "r"(bar), "r"(parity) : "memory");
    return ok != 0;
}
__device__ __forceinline__ void mbar_wait(uint32_t bar, uint32_t parity) {
    if (mbar_try_wait(bar, parity)) return;
#pragma unroll 1
    for (int it = 0; it < (1 << 24); it++) {
        if (mbar_try_wait(bar, parity)) return;
    }
    __trap();
}
__device__ __forceinline__ void tma_load_2d(uint32_t smem_dst, const CUtensorMap* tm, uint32_t bar, int c0, int c1) {
    asm volatile(
        "cp.async.bulk.tensor.2d.shared::cluster.global.mbarrier::complete_tx::bytes [%0], [%1, {%3, %4}], [%2];"
        ::"r"(smem_dst), "l"((uint64_t)tm), "r"(bar), "r"(c0), "r"(c1) : "memory");
}
__device__ __forceinline__ void tma_load_2d_mc(uint32_t smem_dst, const CUtensorMap* tm, uint32_t bar, int c0, int c1,
                                               uint16_t mask) {
    asm volatile(
        "cp.async.bulk.tensor.2d.shared::cluster.global.mbarrier::complete_tx::bytes.multicast::cluster [%0], [%1, {%3, %4}], [%2], %5;"
        ::"r"(smem_dst), "l"((uint64_t)tm), "r"(bar), "r"(c0), "r"(c1), "h"(mask) : "memory");
}
__device__ __forceinline__ void mbar_arrive_cluster(uint32_t local_bar, uint32_t cta) {
    asm volatile(
        "{\n"
        ".reg .b32 ra;\n"
        "mapa.shared::cluster.u32 ra, %0, %1;\n"
        "mbarrier.arrive.shared::cluster.b64 _, [ra];\n"
        "}\n" ::"r"(local_bar), "r"(cta) : "memory");
}
__device__ __forceinline__ void cluster_arrive() { asm volatile("barrier.cluster.arrive.relaxed.aligned;" ::: "memory"); }
__device__ __forceinline__ void fence_async_s() { asm volatile("fence.proxy.async.shared::cta;" ::: "memory"); }
__device__ __forceinline__ void fence_async_g() { asm volatile("fence.proxy.async.global;" ::: "memory"); }
__device__ __forceinline__ void cluster_wait() { asm volatile("barrier.cluster.wait.acquire.aligned;" ::: "memory"); }
__device__ __forceinline__ void pdl_wait() { asm volatile("griddepcontrol.wait;" ::: "memory"); }
__device__ __forceinline__ void pdl_launch() { asm volatile("griddepcontrol.launch_dependents;" ::: "memory"); }
__device__ __forceinline__ void wgmma_fence() { asm volatile("wgmma.fence.sync.aligned;" ::: "memory"); }
__device__ __forceinline__ void wgmma_commit() { asm volatile("wgmma.commit_group.sync.aligned;" ::: "memory"); }
template <int N>
__device__ __forceinline__ void wgmma_wait() { asm volatile("wgmma.wait_group.sync.aligned %0;" ::"n"(N) : "memory"); }

__device__ __forceinline__ uint64_t make_desc(uint32_t saddr, uint32_t lbo_bytes, uint32_t sbo_bytes) {
    uint64_t d = 0;
    d |= (uint64_t)((saddr & 0x3FFFF) >> 4);
    d |= (uint64_t)((lbo_bytes & 0x3FFFF) >> 4) << 16;
    d |= (uint64_t)((sbo_bytes & 0x3FFFF) >> 4) << 32;
    d |= (uint64_t)1 << 62;
    return d;
}

__device__ __forceinline__ void wgmma_m64n128k16(float (&d)[64], uint64_t da, uint64_t db, int scale_d) {
    asm volatile(
        "{\n"
        ".reg .pred p;\n"
        "setp.ne.b32 p, %66, 0;\n"
        "wgmma.mma_async.sync.aligned.m64n128k16.f32.bf16.bf16 "
        "{%0,%1,%2,%3,%4,%5,%6,%7,%8,%9,%10,%11,%12,%13,%14,%15,%16,%17,%18,%19,%20,%21,%22,%23,%24,%25,%26,%27,%28,%29,%30,%31,%32,%33,%34,%35,%36,%37,%38,%39,%40,%41,%42,%43,%44,%45,%46,%47,%48,%49,%50,%51,%52,%53,%54,%55,%56,%57,%58,%59,%60,%61,%62,%63},"
        " %64, %65, p, 1, 1, 0, 1;\n"
        "}\n"
        : "+f"(d[0]), "+f"(d[1]), "+f"(d[2]), "+f"(d[3]), "+f"(d[4]), "+f"(d[5]), "+f"(d[6]), "+f"(d[7]), "+f"(d[8]), "+f"(d[9]), "+f"(d[10]), "+f"(d[11]), "+f"(d[12]), "+f"(d[13]), "+f"(d[14]), "+f"(d[15]), "+f"(d[16]), "+f"(d[17]), "+f"(d[18]), "+f"(d[19]), "+f"(d[20]), "+f"(d[21]), "+f"(d[22]), "+f"(d[23]), "+f"(d[24]), "+f"(d[25]), "+f"(d[26]), "+f"(d[27]), "+f"(d[28]), "+f"(d[29]), "+f"(d[30]), "+f"(d[31]), "+f"(d[32]), "+f"(d[33]), "+f"(d[34]), "+f"(d[35]), "+f"(d[36]), "+f"(d[37]), "+f"(d[38]), "+f"(d[39]), "+f"(d[40]), "+f"(d[41]), "+f"(d[42]), "+f"(d[43]), "+f"(d[44]), "+f"(d[45]), "+f"(d[46]), "+f"(d[47]), "+f"(d[48]), "+f"(d[49]), "+f"(d[50]), "+f"(d[51]), "+f"(d[52]), "+f"(d[53]), "+f"(d[54]), "+f"(d[55]), "+f"(d[56]), "+f"(d[57]), "+f"(d[58]), "+f"(d[59]), "+f"(d[60]), "+f"(d[61]), "+f"(d[62]), "+f"(d[63])
        : "l"(da), "l"(db), "r"(scale_d));
}

__device__ __forceinline__ void wgmma_n128p(float* d, uint64_t da, uint64_t db, int scale_d) {
    asm volatile(
        "{\n"
        ".reg .pred p;\n"
        "setp.ne.b32 p, %66, 0;\n"
        "wgmma.mma_async.sync.aligned.m64n128k16.f32.bf16.bf16 "
        "{%0,%1,%2,%3,%4,%5,%6,%7,%8,%9,%10,%11,%12,%13,%14,%15,%16,%17,%18,%19,%20,%21,%22,%23,%24,%25,%26,%27,%28,%29,%30,%31,%32,%33,%34,%35,%36,%37,%38,%39,%40,%41,%42,%43,%44,%45,%46,%47,%48,%49,%50,%51,%52,%53,%54,%55,%56,%57,%58,%59,%60,%61,%62,%63},"
        " %64, %65, p, 1, 1, 0, 1;\n"
        "}\n"
        : "+f"(d[0]), "+f"(d[1]), "+f"(d[2]), "+f"(d[3]), "+f"(d[4]), "+f"(d[5]), "+f"(d[6]), "+f"(d[7]), "+f"(d[8]), "+f"(d[9]), "+f"(d[10]), "+f"(d[11]), "+f"(d[12]), "+f"(d[13]), "+f"(d[14]), "+f"(d[15]), "+f"(d[16]), "+f"(d[17]), "+f"(d[18]), "+f"(d[19]), "+f"(d[20]), "+f"(d[21]), "+f"(d[22]), "+f"(d[23]), "+f"(d[24]), "+f"(d[25]), "+f"(d[26]), "+f"(d[27]), "+f"(d[28]), "+f"(d[29]), "+f"(d[30]), "+f"(d[31]), "+f"(d[32]), "+f"(d[33]), "+f"(d[34]), "+f"(d[35]), "+f"(d[36]), "+f"(d[37]), "+f"(d[38]), "+f"(d[39]), "+f"(d[40]), "+f"(d[41]), "+f"(d[42]), "+f"(d[43]), "+f"(d[44]), "+f"(d[45]), "+f"(d[46]), "+f"(d[47]), "+f"(d[48]), "+f"(d[49]), "+f"(d[50]), "+f"(d[51]), "+f"(d[52]), "+f"(d[53]), "+f"(d[54]), "+f"(d[55]), "+f"(d[56]), "+f"(d[57]), "+f"(d[58]), "+f"(d[59]), "+f"(d[60]), "+f"(d[61]), "+f"(d[62]), "+f"(d[63])
        : "l"(da), "l"(db), "r"(scale_d));
}
__device__ __forceinline__ void wgmma_n96p(float* d, uint64_t da, uint64_t db, int scale_d) {
    asm volatile(
        "{\n"
        ".reg .pred p;\n"
        "setp.ne.b32 p, %50, 0;\n"
        "wgmma.mma_async.sync.aligned.m64n96k16.f32.bf16.bf16 "
        "{%0,%1,%2,%3,%4,%5,%6,%7,%8,%9,%10,%11,%12,%13,%14,%15,%16,%17,%18,%19,%20,%21,%22,%23,%24,%25,%26,%27,%28,%29,%30,%31,%32,%33,%34,%35,%36,%37,%38,%39,%40,%41,%42,%43,%44,%45,%46,%47},"
        " %48, %49, p, 1, 1, 0, 1;\n"
        "}\n"
        : "+f"(d[0]), "+f"(d[1]), "+f"(d[2]), "+f"(d[3]), "+f"(d[4]), "+f"(d[5]), "+f"(d[6]), "+f"(d[7]), "+f"(d[8]), "+f"(d[9]), "+f"(d[10]), "+f"(d[11]), "+f"(d[12]), "+f"(d[13]), "+f"(d[14]), "+f"(d[15]), "+f"(d[16]), "+f"(d[17]), "+f"(d[18]), "+f"(d[19]), "+f"(d[20]), "+f"(d[21]), "+f"(d[22]), "+f"(d[23]), "+f"(d[24]), "+f"(d[25]), "+f"(d[26]), "+f"(d[27]), "+f"(d[28]), "+f"(d[29]), "+f"(d[30]), "+f"(d[31]), "+f"(d[32]), "+f"(d[33]), "+f"(d[34]), "+f"(d[35]), "+f"(d[36]), "+f"(d[37]), "+f"(d[38]), "+f"(d[39]), "+f"(d[40]), "+f"(d[41]), "+f"(d[42]), "+f"(d[43]), "+f"(d[44]), "+f"(d[45]), "+f"(d[46]), "+f"(d[47])
        : "l"(da), "l"(db), "r"(scale_d));
}

__device__ __forceinline__ void wgmma_rs32h(float* d, uint32_t a0, uint32_t a1, uint32_t a2, uint32_t a3, uint64_t db, int scale_d) {
    asm volatile(
        "{\n"
        ".reg .pred p;\n"
        "setp.ne.b32 p, %21, 0;\n"
        "wgmma.mma_async.sync.aligned.m64n32k16.f32.f16.f16 "
        "{%0,%1,%2,%3,%4,%5,%6,%7,%8,%9,%10,%11,%12,%13,%14,%15},"
        " {%16,%17,%18,%19}, %20, p, 1, 1, 0;\n"
        "}\n"
        : "+f"(d[0]), "+f"(d[1]), "+f"(d[2]), "+f"(d[3]), "+f"(d[4]), "+f"(d[5]), "+f"(d[6]), "+f"(d[7]), "+f"(d[8]), "+f"(d[9]), "+f"(d[10]), "+f"(d[11]), "+f"(d[12]), "+f"(d[13]), "+f"(d[14]), "+f"(d[15])
        : "r"(a0), "r"(a1), "r"(a2), "r"(a3), "l"(db), "r"(scale_d));
}

constexpr int CB = 64;
constexpr int CONV_CH = 4;
constexpr int KP_LEN = 672;
constexpr int KPO_OFF = KP_LEN + 16;
constexpr int UR_REAL = L_SEQ;
constexpr int UR_PITCH = 6144;
constexpr int UR_BYTES = 3 * UR_PITCH + 41 * 128;
__device__ __align__(1024) __half g_ur[D_MODEL * UR_REAL];
constexpr int KH_LEN = 648;

constexpr int TROW = 264;
constexpr int TROWS = 24;
struct PrepSmemLN { __half tile[16][D_MODEL + 8]; };

__device__ __forceinline__ void mma_16816(float (&c)[4], uint32_t a0, uint32_t a1, uint32_t a2, uint32_t a3,
                                          uint32_t b0, uint32_t b1) {
    asm volatile(
        "mma.sync.aligned.m16n8k16.row.col.f32.f16.f16.f32 {%0,%1,%2,%3}, {%4,%5,%6,%7}, {%8,%9}, {%0,%1,%2,%3};"
        : "+f"(c[0]), "+f"(c[1]), "+f"(c[2]), "+f"(c[3])
        : "r"(a0), "r"(a1), "r"(a2), "r"(a3), "r"(b0), "r"(b1));
}
__device__ __forceinline__ void ldsm_x4(uint32_t addr, uint32_t& r0, uint32_t& r1, uint32_t& r2, uint32_t& r3) {
    asm volatile("ldmatrix.sync.aligned.m8n8.x4.shared.b16 {%0,%1,%2,%3}, [%4];"
                 : "=r"(r0), "=r"(r1), "=r"(r2), "=r"(r3) : "r"(addr));
}
__device__ __forceinline__ void ldsm_x2(uint32_t addr, uint32_t& r0, uint32_t& r1) {
    asm volatile("ldmatrix.sync.aligned.m8n8.x2.shared.b16 {%0,%1}, [%2];" : "=r"(r0), "=r"(r1) : "r"(addr));
}
__device__ __forceinline__ void bar_sync(int id, int n) { asm volatile("bar.sync %0, %1;" ::"r"(id), "r"(n) : "memory"); }

__device__ __forceinline__ float2 cexp_fast(float re, float im) {
    float e = __expf(re);
    float t = im * 0.15915494309189535f;
    t -= rintf(t);
    float ang = t * 6.283185307179586f;
    return make_float2(e * __cosf(ang), e * __sinf(ang));
}
__device__ __forceinline__ float2 cmul(float2 a, float2 b) {
    return make_float2(a.x * b.x - a.y * b.y, a.x * b.y + a.y * b.x);
}
__device__ __forceinline__ int kidx(int j) {
    int r = max(0, 24 - __clz(j));
    int q = (j + ((1 << r) >> 1) - 1 + ((j >> r) & 1)) >> r;
    if (r == 0) q = j;
    return 128 * r + q;
}

constexpr int XH_PITCH = (D_MODEL + 8) * 2;
__device__ __forceinline__ void ln_block(const __nv_bfloat16* __restrict__ x, uint32_t xb, uint32_t xh, int blk) {
    const int warp = threadIdx.x >> 5;
    const int lane = threadIdx.x & 31;
    uint4 tin[2][2];
#pragma unroll
    for (int rr = 0; rr < 2; rr++) {
        const uint4* xr = reinterpret_cast<const uint4*>(x + (size_t)(blk * 16 + warp * 2 + rr) * D_MODEL);
        tin[rr][0] = xr[lane];
        tin[rr][1] = xr[lane + 32];
    }
    auto lo = [](uint32_t w) { return __uint_as_float(w << 16); };
    auto hi = [](uint32_t w) { return __uint_as_float(w & 0xffff0000u); };
    float s[2], q[2], c[2];
#pragma unroll
    for (int rr = 0; rr < 2; rr++) c[rr] = __shfl_sync(0xffffffffu, lo(tin[rr][0].x), 0);
#pragma unroll
    for (int rr = 0; rr < 2; rr++) {
        const uint32_t* w = reinterpret_cast<const uint32_t*>(&tin[rr][0]);
        float a0 = 0.f, a1 = 0.f, b0 = 0.f, b1 = 0.f;
#pragma unroll
        for (int i = 0; i < 8; i++) {
            float d0 = lo(w[i]) - c[rr], d1 = hi(w[i]) - c[rr];
            a0 += d0;
            a1 += d1;
            b0 = fmaf(d0, d0, b0);
            b1 = fmaf(d1, d1, b1);
        }
        s[rr] = a0 + a1;
        q[rr] = b0 + b1;
    }
#pragma unroll
    for (int o = 16; o > 0; o >>= 1)
#pragma unroll
        for (int rr = 0; rr < 2; rr++) {
            s[rr] += __shfl_xor_sync(0xffffffffu, s[rr], o);
            q[rr] += __shfl_xor_sync(0xffffffffu, q[rr], o);
        }
    if (threadIdx.x == 32) TS(4, 5);
#pragma unroll
    for (int rr = 0; rr < 2; rr++) {
        const int row = warp * 2 + rr;
        const float md = s[rr] * (1.0f / D_MODEL);
        const float var = bf16r(fmaxf(q[rr] * (1.0f / D_MODEL) - md * md, 0.f));
        const float mb = bf16r(c[rr] + md);
        const float sd = bf16r(sqrtf(bf16r(var + 1e-5f)));
        const float rs = 1.0f / sd;
        const __nv_bfloat162 mb2 = __floats2bfloat162_rn(mb, mb);
#pragma unroll
        for (int i = 0; i < 2; i++) {
            const __nv_bfloat162* w = reinterpret_cast<const __nv_bfloat162*>(&tin[rr][i]);
            uint32_t t[4], th[4];
#pragma unroll
            for (int j = 0; j < 4; j++) {
                __nv_bfloat162 d = __hsub2(w[j], mb2);
                uint32_t du = *reinterpret_cast<uint32_t*>(&d);
                __nv_bfloat162 v = __floats2bfloat162_rn(lo(du) * rs, hi(du) * rs);
                t[j] = *reinterpret_cast<uint32_t*>(&v);
                __half2 vh = __floats2half2_rn(lo(t[j]), hi(t[j]));
                th[j] = *reinterpret_cast<uint32_t*>(&vh);
            }
            *reinterpret_cast<uint4*>(g_xn + (size_t)(blk * 16 + row) * D_MODEL + (lane + 32 * i) * 8) = make_uint4(t[0], t[1], t[2], t[3]);
            asm volatile("st.shared.v4.b32 [%0], {%1,%2,%3,%4};" ::"r"(xh + (uint32_t)((15 - row) * XH_PITCH + (lane + 32 * i) * 16)),
                         "r"(th[0]), "r"(th[1]), "r"(th[2]), "r"(th[3]) : "memory");
        }
    }
    if (threadIdx.x == 32) TS(4, 6);
    bar_sync(1, 288);
    if (threadIdx.x == 32) TS(4, 8);
}
__device__ __forceinline__ void ln_block2(uint32_t xh, uint32_t xt, int swp) {
    const int warp = threadIdx.x >> 5;
    const int lane = threadIdx.x & 31;
    const uint32_t src = xh + (uint32_t)(((lane & 7) + 8 * ((lane >> 3) & 1)) * XH_PITCH + (128 * warp + 8 * (lane >> 4)) * 2);
    const uint32_t dst = xt + (uint32_t)((128 * warp + 8 * (lane >> 4) + (lane & 7)) * 32 + (((lane >> 3) & 1) ^ swp) * 16);
#pragma unroll
    for (int i = 0; i < 8; i++) {
        uint32_t r0, r1, r2, r3;
        asm volatile("ldmatrix.sync.aligned.m8n8.x4.trans.shared.b16 {%0,%1,%2,%3}, [%4];"
                     : "=r"(r0), "=r"(r1), "=r"(r2), "=r"(r3) : "r"(src + i * 32) : "memory");
        asm volatile("stmatrix.sync.aligned.m8n8.x4.shared.b16 [%0], {%1,%2,%3,%4};"
                     ::"r"(dst + i * 512), "r"(r0), "r"(r1), "r"(r2), "r"(r3) : "memory");
    }
}

struct KgenIn { uint2 v0, v1, v2, v3; __nv_bfloat16 ldt; };
__device__ __forceinline__ KgenIn kgen_load(const __nv_bfloat16* __restrict__ logAr, const __nv_bfloat16* __restrict__ Aim,
                                            const __nv_bfloat16* __restrict__ Cre, const __nv_bfloat16* __restrict__ Cim,
                                            const __nv_bfloat16* __restrict__ logdt, int d) {
    const int lane = threadIdx.x & 31;
    KgenIn k;
    k.v0 = *reinterpret_cast<const uint2*>(logAr + d * N_STATE + 4 * lane);
    k.v1 = *reinterpret_cast<const uint2*>(Aim + d * N_STATE + 4 * lane);
    k.v2 = *reinterpret_cast<const uint2*>(Cre + d * N_STATE + 4 * lane);
    k.v3 = *reinterpret_cast<const uint2*>(Cim + d * N_STATE + 4 * lane);
    k.ldt = logdt[d];
    return k;
}
__device__ __forceinline__ float kgen_warp(const KgenIn& kin, __half* T, __half* kh, int p0, int p1) {
    const int lane = threadIdx.x & 31;
    const int g = lane >> 2, t4 = lane & 3;
    float are[4], aim[4];
    float2 Cc[4];
    {
        uint2 v0 = kin.v0, v1 = kin.v1, v2 = kin.v2, v3 = kin.v3;
        const float dt = bf16r(expf(__bfloat162float(kin.ldt)));
        const __nv_bfloat16* p0 = reinterpret_cast<const __nv_bfloat16*>(&v0);
        const __nv_bfloat16* p1 = reinterpret_cast<const __nv_bfloat16*>(&v1);
        const __nv_bfloat16* p2 = reinterpret_cast<const __nv_bfloat16*>(&v2);
        const __nv_bfloat16* p3 = reinterpret_cast<const __nv_bfloat16*>(&v3);
#pragma unroll
        for (int i = 0; i < 4; i++) {
            are[i] = -bf16r(expf(__bfloat162float(p0[i]))) * dt;
            aim[i] = __bfloat162float(p1[i]) * dt;
            Cc[i] = make_float2(__bfloat162float(p2[i]) * dt, __bfloat162float(p3[i]) * dt);
        }
    }
    if (threadIdx.x == 128) TS(7, 8);
    float mx = 0.f;
#pragma unroll
    for (int i = 0; i < 4; i++) mx = fmaxf(mx, fmaxf(fabsf(Cc[i].x), fabsf(Cc[i].y)));
#pragma unroll
    for (int o = 16; o > 0; o >>= 1) mx = fmaxf(mx, __shfl_xor_sync(0xffffffffu, mx, o));
    float scale = 1.0f;
    if (mx > 0.f && mx < 3.0e38f) {
        int e;
        frexpf(mx, &e);
        e = max(-120, min(120, e));
        scale = ldexpf(1.0f, -e);
    }
#pragma unroll
    for (int i = 0; i < 4; i++) {
        Cc[i].x *= scale;
        Cc[i].y *= scale;
    }
    const uint32_t abase = smem_u32(T) + (uint32_t)(((lane & 7) + ((lane >> 3) & 1) * 8) * TROW + (lane >> 4) * 8) * 2;
    const uint32_t bbase = smem_u32(T) + (uint32_t)((16 + (lane & 7)) * TROW + ((lane >> 3) & 3) * 8) * 2;
    if (threadIdx.x == 128) TS(7, 9);
    float2 w[4], ratio[4], z[4], zs[4];
    const float pb = p0 == 0 ? 0.f : (float)(64 << p0), ps = p0 == 0 ? 16.f : (float)(4 << p0);
    const float pz = p0 == 0 ? 1.f : (float)(1 << (p0 - 1));
#pragma unroll
    for (int i = 0; i < 4; i++) {
        w[i] = cmul(make_float2(Cc[i].x, -Cc[i].y), cexp_fast(are[i] * pb, -aim[i] * pb));
        ratio[i] = cexp_fast(are[i] * ps, -aim[i] * ps);
        zs[i] = cexp_fast(are[i] * pz, aim[i] * pz);
        z[i] = make_float2(1.f, 0.f);
    }
    if (threadIdx.x == 256) TS(5, 0);
    if (threadIdx.x == 128) TS(7, 1);
#pragma unroll 1
    for (int pass = p0; pass < p1; pass++) {
        const int r = pass <= 1 ? 0 : pass - 1;
        if (pass >= 2 && pass != p0) {
#pragma unroll
            for (int i = 0; i < 4; i++) {
                if (pass >= 3) ratio[i] = cmul(ratio[i], ratio[i]);
                zs[i] = cmul(zs[i], zs[i]);
                z[i] = make_float2(1.f, 0.f);
            }
        }
        if (pass != 1) {
#pragma unroll
            for (int hi = 0; hi < 16; hi++) {
                uint4 v;
                __half2* pv = reinterpret_cast<__half2*>(&v);
#pragma unroll
                for (int i = 0; i < 4; i++) {
                    pv[i] = __floats2half2_rn(w[i].x, w[i].y);
                    w[i] = cmul(w[i], ratio[i]);
                }
                *reinterpret_cast<uint4*>(&T[hi * TROW + 8 * lane]) = v;
            }
        }
        {
#pragma unroll
            for (int lo = 0; lo < 8; lo++) {
                uint4 v;
                __half2* pv = reinterpret_cast<__half2*>(&v);
#pragma unroll
                for (int i = 0; i < 4; i++) {
                    pv[i] = __floats2half2_rn(z[i].x, z[i].y);
                    z[i] = cmul(z[i], zs[i]);
                }
                *reinterpret_cast<uint4*>(&T[(16 + lo) * TROW + 8 * lane]) = v;
            }
        }
        __syncwarp();
        if (threadIdx.x == 256) TS(5, 1 + 2 * pass);
        if (threadIdx.x == 128) TS(7, 2);
        float acc[4][4];
#pragma unroll
        for (int i = 0; i < 4; i++)
#pragma unroll
            for (int k = 0; k < 4; k++) acc[i][k] = 0.f;
#pragma unroll
        for (int kt = 0; kt < 16; kt += 2) {
            uint32_t a0, a1, a2, a3, a4, a5, a6, a7, b0, b1, b2, b3;
            ldsm_x4(abase + kt * 32, a0, a1, a2, a3);
            ldsm_x4(abase + kt * 32 + 32, a4, a5, a6, a7);
            ldsm_x4(bbase + kt * 32, b0, b1, b2, b3);
            mma_16816(acc[kt & 3], a0, a1, a2, a3, b0, b1);
            mma_16816(acc[(kt & 3) + 1], a4, a5, a6, a7, b2, b3);
        }
        {
            const int nlo = (r == 0) ? 16 : 8;
            const int obase = (r == 0) ? pass * 8 : (256 + (r - 1) * 128);
            float s0 = 2.0f * ((acc[0][0] + acc[1][0]) + (acc[2][0] + acc[3][0]));
            float s1 = 2.0f * ((acc[0][1] + acc[1][1]) + (acc[2][1] + acc[3][1]));
            float s2 = 2.0f * ((acc[0][2] + acc[1][2]) + (acc[2][2] + acc[3][2]));
            float s3 = 2.0f * ((acc[0][3] + acc[1][3]) + (acc[2][3] + acc[3][3]));
            *reinterpret_cast<__half2*>(&kh[obase + g * nlo + 2 * t4]) = __floats2half2_rn(s0, s1);
            *reinterpret_cast<__half2*>(&kh[obase + (g + 8) * nlo + 2 * t4]) = __floats2half2_rn(s2, s3);
        }
        __syncwarp();
        if (threadIdx.x == 256) TS(5, 2 + 2 * pass);
    }
    if (p1 == 5) {
        float k2048 = (w[0].x + w[1].x) + (w[2].x + w[3].x);
#pragma unroll
        for (int o = 16; o > 0; o >>= 1) k2048 += __shfl_xor_sync(0xffffffffu, k2048, o);
        if (lane == 0) kh[640] = __float2half_rn(2.0f * k2048);
    }
    return 1.0f / scale;
}

__device__ __forceinline__ void kexpand_warp(const __half* kh, __half* dstE) {
    const int lane = threadIdx.x & 31;
    __half* dstO = dstE + KPO_OFF;
    const uint32_t* kw = reinterpret_cast<const uint32_t*>(kh);
    const unsigned short* ks = reinterpret_cast<const unsigned short*>(kh);
    auto dup = [](uint32_t v) -> uint32_t { return v | (v << 16); };
    {
        const int m = lane;
        uint4 v = *reinterpret_cast<const uint4*>(kh + 8 * m);
        uint32_t w = kw[4 * m + 4];
        if (m == 31) w = __byte_perm(w, w, 0x1010);
        *reinterpret_cast<uint4*>(&dstE[8 * m + 64]) = make_uint4(__byte_perm(v.x, v.y, 0x5432), __byte_perm(v.y, v.z, 0x5432),
                                                                  __byte_perm(v.z, v.w, 0x5432), __byte_perm(v.w, w, 0x5432));
        *reinterpret_cast<uint4*>(&dstO[8 * m + 64]) = make_uint4(v.y, v.z, v.w, w);
    }
    {
        const int m = 32 + lane;
        uint2 v = *reinterpret_cast<const uint2*>(kh + 128 + 4 * m);
        uint32_t a4 = dup(ks[128 + 4 * m + 4]);
        uint32_t a22 = __byte_perm(v.y, v.y, 0x1010);
        *reinterpret_cast<uint4*>(&dstE[8 * m + 64]) = make_uint4(v.x, a22, v.y, a4);
        *reinterpret_cast<uint4*>(&dstO[8 * m + 64]) = make_uint4(__byte_perm(v.x, v.y, 0x5432), a22, __byte_perm(v.y, a4, 0x5432), a4);
    }
    if (lane < 20) {
        const int m = lane < 8 ? lane - 8 : 56 + lane;
        uint32_t k01 = kw[0], kl = ks[384];
        uint32_t e3 = (m == -1) ? (k01 << 16) : 0u, o3 = (m == -1) ? k01 : 0u;
        uint32_t e0 = (m == 64) ? dup(kl) : 0u, o0 = (m == 64) ? kl : 0u;
        *reinterpret_cast<uint4*>(&dstE[8 * m + 64]) = make_uint4(e0, 0u, 0u, e3);
        *reinterpret_cast<uint4*>(&dstO[8 * m + 64]) = make_uint4(o0, 0u, 0u, o3);
    }
}

constexpr int BM = 128, BK = 64;
constexpr int G1_BN = 224, G1_ST = 3;
constexpr int G1_STAGE = BM * BK * 2 + BK * 256 * 2;
constexpr int G1_EPITCH = G1_BN * 2 + 16;
constexpr int YS_PAD = 32;
constexpr int VR_BYTES = 6208;
constexpr int DB_BYTES = 6496;
struct ConvSmem {
    __align__(1024) unsigned char ur[UR_BYTES];
    union {
        struct {
            __align__(16) unsigned char db[CONV_CH][DB_BYTES];
            __align__(16) unsigned char vr[CONV_CH][VR_BYTES];
            __nv_bfloat16 ylow[512 * CONV_CH + 3 * YS_PAD];
        } a;
        __half T[CONV_CH][TROWS * TROW];
    } u;
    __half kh[CONV_CH][KH_LEN];
};
constexpr int CONV_SMEM = UR_BYTES + CONV_CH * (DB_BYTES + VR_BYTES) + (512 * CONV_CH + 3 * YS_PAD) * 2 + CONV_CH * KH_LEN * 2;
constexpr int KB_SMEM = G1_ST * G1_STAGE + CONV_SMEM;
static_assert(KB_SMEM <= 232448 - 1024, "smem");
static_assert((KPO_OFF + KP_LEN) * 2 <= DB_BYTES, "kp fits");

template <int NCH>
__device__ __forceinline__ void u_prefix(uint32_t urb, int t0, float (&P)[NCH * 8 + 1]) {
    P[0] = 0.f;
#pragma unroll
    for (int ch = 0; ch < NCH; ch++) {
        const int rev = 2040 - (t0 + 8 * ch);
        uint32_t w[4];
        asm volatile("ld.shared.v4.b32 {%0,%1,%2,%3}, [%4];" : "=r"(w[0]), "=r"(w[1]), "=r"(w[2]), "=r"(w[3])
                     : "r"(urb + (uint32_t)((rev >> 6) * 128 + ((((rev >> 3) ^ (rev >> 6)) & 7) << 4))));
#pragma unroll
        for (int i = 0; i < 4; i++) {
            float2 f = __half22float2(*reinterpret_cast<__half2*>(&w[3 - i]));
            P[8 * ch + 2 * i + 1] = P[8 * ch + 2 * i] + f.y;
            P[8 * ch + 2 * i + 2] = P[8 * ch + 2 * i + 1] + f.x;
        }
    }
}
template <int NE, int HI, int LO, int NP>
__device__ __forceinline__ void v_store(uint32_t arr, int c0, const float (&P)[NP]) {
#pragma unroll
    for (int ch = 0; ch < NE / 8; ch++) {
        uint32_t w[4];
#pragma unroll
        for (int i = 0; i < 4; i++) {
            const int e = 8 * ch + 2 * i;
            __half2 h = __floats2half2_rn(P[e + HI] - P[e + LO], P[e + 1 + HI] - P[e + 1 + LO]);
            w[i] = *reinterpret_cast<uint32_t*>(&h);
        }
        const int c = c0 + ch;
        asm volatile("st.shared.v4.b32 [%0], {%1,%2,%3,%4};" ::"r"(arr + (uint32_t)((c ^ ((c >> 3) & 1)) << 4)),
                     "r"(w[0]), "r"(w[1]), "r"(w[2]), "r"(w[3]) : "memory");
    }
}
template <int D0, int ND>
__device__ __forceinline__ void level_set(float (&accL)[6][2][4], const unsigned short* kh, int kbase, int kstr, int phi,
                                          uint32_t baddr) {
    const int lane = threadIdx.x & 31;
    const int pb = 16 * D0 - 8 + (lane >> 2) - 2 * (lane & 3);
    uint32_t F[2 * ND + 1];
#pragma unroll
    for (int m = 0; m < 2 * ND + 1; m++) {
        const int p = pb + 8 * m;
        uint32_t lo = (p >= 16 * D0 && p <= phi) ? kh[kbase + kstr * p] : 0u;
        uint32_t hi = (p - 1 >= 16 * D0 && p - 1 <= phi) ? kh[kbase + kstr * (p - 1)] : 0u;
        F[m] = lo | (hi << 16);
    }
#pragma unroll
    for (int j = 0; j + D0 < 8; j++) {
        uint32_t b[4];
        asm volatile("ldmatrix.sync.aligned.m8n8.x4.trans.shared.b16 {%0,%1,%2,%3}, [%4];"
                     : "=r"(b[0]), "=r"(b[1]), "=r"(b[2]), "=r"(b[3]) : "r"(baddr + j * 512));
#pragma unroll
        for (int dd = 0; dd < ND; dd++) {
            if (j + D0 + dd < 8) {
                mma_16816(accL[j + D0 + dd - 2][0], F[2 * dd + 1], F[2 * dd + 2], F[2 * dd], F[2 * dd + 1], b[0], b[1]);
                mma_16816(accL[j + D0 + dd - 2][1], F[2 * dd + 1], F[2 * dd + 2], F[2 * dd], F[2 * dd + 1], b[2], b[3]);
            }
        }
    }
}

constexpr int FL_LN = 0;
constexpr int FL_H = 16 * 8;
constexpr int FL_HE = FL_H + 32 * 8;
constexpr int FL_Y = FL_HE + 32 * 8;
constexpr int FL_UR = FL_Y + 8 * 8;
constexpr int FL_DONE = FL_UR + 8;
constexpr int FL_TOT = FL_DONE + 8;
__device__ unsigned g_flags[FL_TOT];
__device__ __forceinline__ void flag_add(unsigned* p) {
    asm volatile("fence.proxy.async.global;" ::: "memory");
    asm volatile("red.release.gpu.global.add.u32 [%0], 1;" ::"l"(p) : "memory");
}
__device__ __forceinline__ void flag_rel(unsigned* p) {
    asm volatile("red.release.gpu.global.add.u32 [%0], 1;" ::"l"(p) : "memory");
}
__device__ __forceinline__ void bulk_commit() { asm volatile("cp.async.bulk.commit_group;" ::: "memory"); }
template <int N>
__device__ __forceinline__ void bulk_wait() { asm volatile("cp.async.bulk.wait_group %0;" ::"n"(N) : "memory"); }
__device__ __forceinline__ void bulk_store(void* gdst, uint32_t ssrc, uint32_t bytes) {
    asm volatile("cp.async.bulk.global.shared::cta.bulk_group [%0], [%1], %2;" ::"l"(gdst), "r"(ssrc), "r"(bytes) : "memory");
}
__device__ __forceinline__ void tma_store_2d(const CUtensorMap* tm, uint32_t ssrc, int c0, int c1) {
    asm volatile("cp.async.bulk.tensor.2d.global.shared::cta.bulk_group [%0, {%2, %3}], [%1];"
                 ::"l"((uint64_t)tm), "r"(ssrc), "r"(c0), "r"(c1) : "memory");
}
__device__ __forceinline__ void flag_wait(const unsigned* p, unsigned target) {
#pragma unroll 1
    for (int it = 0; it < (1 << 22); it++) {
        unsigned v;
        asm volatile("ld.acquire.gpu.global.u32 %0, [%1];" : "=r"(v) : "l"(p) : "memory");
        if (v >= target) return;
        __nanosleep(20);
    }
    __trap();
}

constexpr int V3_OFF = 128 * 1024;
constexpr int YT_PITCH = 1040;
constexpr int G2_BN = 128, G2_ST = 5;
constexpr int G2_STAGE = BM * BK * 2 + BK * G2_BN * 2;
constexpr int G2_EPITCH = 64 * 2 + 16;
constexpr int G2_HALF = BM * BK * 2;
constexpr int G2_BOFF = 4 * G2_HALF;
constexpr int G2_A4 = V3_OFF;
constexpr int G2_B4 = (G1_ST * G1_STAGE + UR_BYTES + CONV_CH * DB_BYTES + 1023) / 1024 * 1024;
static_assert(G2_B4 + G2_HALF <= G1_ST * G1_STAGE + UR_BYTES + CONV_CH * (DB_BYTES + VR_BYTES), "stage 4 B tile");
__device__ __forceinline__ int g2_ord(int i) { return (int)((0xDCA9865321B740ull >> (4 * i)) & 15u); }
__device__ __forceinline__ uint32_t g2_a(int s) { return s < 4 ? s * G2_HALF : G2_A4; }
__device__ __forceinline__ uint32_t g2_b(int s) { return s < 4 ? G2_BOFF + s * G2_HALF : G2_B4; }

__global__ void __cluster_dims__(2, 1, 1) __launch_bounds__(512, 1)
mega_kernel(const __grid_constant__ CUtensorMap tmA1, const __grid_constant__ CUtensorMap tmB1,
            const __grid_constant__ CUtensorMap tmA2, const __grid_constant__ CUtensorMap tmB2,
            const __grid_constant__ CUtensorMap tmUR, const __grid_constant__ CUtensorMap tmH64,
            const __grid_constant__ CUtensorMap tmH32,
            const __nv_bfloat16* __restrict__ xin, const __nv_bfloat16* __restrict__ bias1,
            const __nv_bfloat16* __restrict__ bias2, const __nv_bfloat16* __restrict__ dskip,
            const __nv_bfloat16* __restrict__ logAr, const __nv_bfloat16* __restrict__ Aim,
            const __nv_bfloat16* __restrict__ Cre, const __nv_bfloat16* __restrict__ Cim,
            const __nv_bfloat16* __restrict__ logdt, __nv_bfloat16* __restrict__ out,
            const __nv_bfloat16* __restrict__ w1g, const __nv_bfloat16* __restrict__ w2g) {
    constexpr int NKB1 = D_MODEL / BK;
    constexpr int NKB2 = F_HID / BK / 2;
    extern __shared__ __align__(1024) unsigned char smraw[];
    __shared__ __align__(8) uint64_t full1[G1_ST], empty1[G1_ST], full2[G2_ST], empty2[G2_ST], conv_bar[CONV_CH], recv_bar[8],
        ready_bar, y_bar, tail_bar, lv_bar;
    __shared__ __align__(16) __nv_bfloat16 sbias[G1_BN];
    __shared__ __align__(16) float sinv[CONV_CH];
    const uint32_t sbase = smem_u32(smraw);
    if (sbase & 1023u) __trap();
    unsigned char* sgen = smraw;
    const int warp = threadIdx.x >> 5, lane = threadIdx.x & 31;
    const int mtile = blockIdx.x >> 3, jt = blockIdx.x & 7;
    const int m0 = mtile * BM, n0 = jt * G1_BN;
    const int rank = jt & 1;
    ConvSmem& S = *reinterpret_cast<ConvSmem*>(sgen + G1_ST * G1_STAGE);

    if (warp != 12) cluster_arrive();
    const int n2 = (jt >> 1) * G2_BN;
    const int kbase = rank * NKB2 * BK;

    if (warp >= 12) {
        asm volatile("setmaxnreg.dec.sync.aligned.u32 40;");
        if (warp == 12) {
            if (lane < G1_ST) mbar_init(smem_u32(&full1[lane]), 1);
            else if (lane < 2 * G1_ST) mbar_init(smem_u32(&empty1[lane - G1_ST]), 2);
            else if (lane < 11) mbar_init(smem_u32(&full2[lane - 6]), 1);
            else if (lane < 16) mbar_init(smem_u32(&empty2[lane - 11]), 2);
            else if (lane < 20) mbar_init(smem_u32(&conv_bar[lane - 16]), 1);
            else if (lane < 28) {
                mbar_init(smem_u32(&recv_bar[lane - 20]), 1);
                mbar_expect_tx(smem_u32(&recv_bar[lane - 20]), 4096);
            } else if (lane == 28) mbar_init(smem_u32(&ready_bar), 1);
            else if (lane == 29) {
                mbar_init(smem_u32(&y_bar), 1);
                mbar_expect_tx(smem_u32(&y_bar), 16384);
            } else if (lane == 30) mbar_init(smem_u32(&tail_bar), 1);
            else mbar_init(smem_u32(&lv_bar), 4);
            asm volatile("fence.mbarrier_init.release.cluster;" ::: "memory");
            __syncwarp();
            if (lane == 0) {
#pragma unroll 1
                for (int kb = 0; kb < 3; kb++) {
                    mbar_expect_tx(smem_u32(&full1[kb]), G1_STAGE);
#pragma unroll
                    for (int j = 0; j < 4; j++)
                        tma_load_2d(sbase + kb * G1_STAGE + BM * BK * 2 + j * (BK * 128), &tmB1, smem_u32(&full1[kb]), n0 + j * 64, kb * BK);
                }
                asm volatile("cp.async.bulk.prefetch.tensor.2d.L2.global.tile [%0, {%1, %2}];"
                             ::"l"((uint64_t)&tmB1), "r"(n0 + (mtile & 3) * 64), "r"((3 + (mtile >> 2)) * BK) : "memory");
                asm volatile("prefetch.tensormap [%0];" ::"l"((uint64_t)&tmUR) : "memory");
                asm volatile("prefetch.tensormap [%0];" ::"l"((uint64_t)&tmA1) : "memory");
                asm volatile("prefetch.tensormap [%0];" ::"l"((uint64_t)&tmH64) : "memory");
                asm volatile("prefetch.tensormap [%0];" ::"l"((uint64_t)&tmH32) : "memory");
                asm volatile("prefetch.tensormap [%0];" ::"l"((uint64_t)&tmB2) : "memory");
                asm volatile("prefetch.tensormap [%0];" ::"l"((uint64_t)&tmA2) : "memory");
            }
            __syncwarp();
            cluster_arrive();
            asm volatile("bar.arrive 7, 224;" ::: "memory");
            bar_sync(1, 288);
            if (lane == 0) {
                flag_rel(&g_flags[FL_LN + mtile * 8]);
                TS(4, 2);
                flag_wait(&g_flags[FL_LN + mtile * 8], 8);
                TS(4, 3);
                fence_async_g();
                tma_load_2d(sbase, &tmA1, smem_u32(&full1[0]), 0, m0);
                tma_load_2d(sbase + G1_STAGE, &tmA1, smem_u32(&full1[1]), BK, m0);
            }
            __syncwarp();
            asm volatile("bar.arrive 8, 288;" ::: "memory");
            bar_sync(3, 64);
            if (lane == 0) {
                TS(4, 10);
                tma_load_2d(sbase + 2 * G1_STAGE, &tmA1, smem_u32(&full1[2]), 2 * BK, m0);
#pragma unroll 1
                for (int kb = G1_ST; kb < NKB1; kb++) {
                    const int ps = kb % G1_ST;
                    mbar_wait(smem_u32(&empty1[ps]), (kb / G1_ST - 1) & 1);
                    uint32_t fb = smem_u32(&full1[ps]);
                    mbar_expect_tx(fb, G1_STAGE);
                    uint32_t pa = sbase + ps * G1_STAGE;
                    uint32_t pb = pa + BM * BK * 2;
                    tma_load_2d(pa, &tmA1, fb, kb * BK, m0);
#pragma unroll
                    for (int j = 0; j < 4; j++) tma_load_2d(pb + j * (BK * 128), &tmB1, fb, n0 + j * 64, kb * BK);
                    if (kb == 4) {
                        constexpr int SH = D_MODEL * F_HID / 128;
                        asm volatile("cp.async.bulk.prefetch.L2.global [%0], %1;" ::"l"(w2g + (size_t)blockIdx.x * SH), "r"(SH * 2) : "memory");
                    }
                }
#pragma unroll 1
                for (int i = 0; i < 4; i++) {
                    const int kb = i ^ 2;
                    if (i == 0) {
                        mbar_wait(smem_u32(&empty1[2]), 1);
                        mbar_arrive(smem_u32(&tail_bar));
                    }
                    if (i == 2) mbar_wait(smem_u32(&empty1[1]), 0);
                    uint32_t fb = smem_u32(&full2[kb]);
                    mbar_expect_tx(fb, G2_STAGE);
                    uint32_t sb = sbase + G2_BOFF + kb * G2_HALF;
#pragma unroll
                    for (int j = 0; j < 2; j++) tma_load_2d(sb + j * (BK * 128), &tmB2, fb, n2 + j * 64, kbase + g2_ord(kb) * BK);
                }
            }
            __syncwarp();
            bar_sync(4, 288);
            if (lane == 0) {
                TS(2, 8);
                flag_wait(&g_flags[FL_HE + (mtile * 2 + rank) * 8], 32);
                fence_async_g();
#pragma unroll 1
                for (int kb = 2; kb < 4; kb++)
                    tma_load_2d(sbase + kb * G2_HALF, &tmA2, smem_u32(&full2[kb]), kbase + g2_ord(kb) * BK, m0);
                flag_wait(&g_flags[FL_H + (mtile * 2 + rank) * 8], 32);
                TS(2, 9);
                fence_async_g();
#pragma unroll 1
                for (int kb = 4; kb < NKB2; kb++) {
                    const int ps = kb % G2_ST;
                    if (kb == 4) mbar_wait(smem_u32(&lv_bar), 0);
                    else mbar_wait(smem_u32(&empty2[ps]), (kb / G2_ST - 1) & 1);
                    uint32_t fb = smem_u32(&full2[ps]);
                    mbar_expect_tx(fb, G2_STAGE);
                    uint32_t pa = sbase + g2_a(ps);
                    uint32_t pb = sbase + g2_b(ps);
                    const int kc = kbase + g2_ord(kb) * BK;
                    tma_load_2d(pa, &tmA2, fb, kc, m0);
#pragma unroll
                    for (int j = 0; j < 2; j++) tma_load_2d(pb + j * (BK * 128), &tmB2, fb, n2 + j * 64, kc);
                }
            }
            __syncwarp();
        } else {
            if (warp == 13) {
                const void* pa = g_flags;
                switch (lane) {
                    case 0: pa = g_xn + (size_t)blockIdx.x * 16 * D_MODEL; break;
                    case 1: pa = g_xn + (size_t)m0 * D_MODEL; break;
                    case 2: pa = g_ur; break;
                    case 3: pa = g_ur + (size_t)(D_MODEL - 1) * UR_REAL; break;
                    case 4: pa = g_ur + (size_t)blockIdx.x * CONV_CH * UR_REAL; break;
                    case 5: pa = g_h + (size_t)m0 * F_HID; break;
                    case 6: pa = g_h + (size_t)(m0 + BM - 1) * F_HID; break;
                    case 7: pa = g_s + (size_t)blockIdx.x * L_SEQ * CONV_CH; break;
                    case 8: pa = g_s + (size_t)(jt * 16) * L_SEQ * CONV_CH; break;
                    case 9: pa = out + (size_t)m0 * D_MODEL; break;
                    case 10: pa = w1g; break;
                    case 11: pa = w1g + (size_t)(D_MODEL - 1) * F_HID; break;
                    case 12: pa = w2g + (size_t)kbase * D_MODEL; break;
                    case 13: pa = w2g + (size_t)(kbase + NKB2 * BK - 1) * D_MODEL; break;
                    case 14: pa = bias1; break;
                    case 15: pa = bias2; break;
                    case 16: pa = dskip; break;
                    case 17: pa = g_xn + (size_t)(m0 + BM - 1) * D_MODEL; break;
                    case 18: pa = out + (size_t)(m0 + BM - 1) * D_MODEL; break;
                    case 19: pa = g_s + (size_t)(jt * 16 + 15) * L_SEQ * CONV_CH; break;
                    default: break;
                }
                asm volatile("prefetch.global.L2 [%0];" ::"l"(pa));
            }
            if (warp == 13) {
                bar_sync(2, 160);
                if (lane == 0) {
                    const int r0 = L_SEQ - 16 - blockIdx.x * 16;
                    const int xc = (r0 & ~63) + ((((r0 >> 3) ^ (r0 >> 6)) & 6) << 3);
                    tma_store_2d(&tmUR, sbase + 2 * G1_STAGE, xc, 0);
                    tma_store_2d(&tmUR, sbase + 2 * G1_STAGE + 8192, xc, 256);
                    bulk_commit();
                    asm volatile("cp.async.bulk.wait_group.read 0;" ::: "memory");
                }
                __syncwarp();
                asm volatile("bar.arrive 3, 64;" ::: "memory");
                if (lane == 0) {
                    TS(7, 5);
                    bulk_wait<0>();
                    flag_add(&g_flags[FL_UR]);
                    TS(4, 1);
                    flag_wait(&g_flags[FL_UR], 128);
                    TS(4, 9);
                    fence_async_g();
                }
                __syncwarp();
                if (lane == 0) {
#pragma unroll 1
                    for (int c = 0; c < CONV_CH; c++) {
                        uint32_t cb = smem_u32(&conv_bar[c]);
                        mbar_expect_tx(cb, UR_REAL * 2);
                        asm volatile("cp.async.bulk.shared::cluster.global.mbarrier::complete_tx::bytes [%0], [%1], %2, [%3];"
                                     ::"r"(smem_u32(&S.ur[c * UR_PITCH])), "l"(g_ur + (size_t)(blockIdx.x * CONV_CH + c) * UR_REAL),
                                       "r"(UR_REAL * 2), "r"(cb) : "memory");
                    }
                }
                __syncwarp();
                bar_sync(12, 288);
                if (lane < 8) {
                    tma_store_2d(&tmH64, sbase + lane * 3072, n0, m0 + lane * 16);
                    tma_store_2d(&tmH32, sbase + lane * 3072 + 2048, n0 + 64, m0 + lane * 16);
                    bulk_commit();
                    bulk_wait<0>();
                    flag_add(&g_flags[FL_HE + (mtile * 2 + (jt >> 2)) * 8]);
                }
                __syncwarp();
                if (lane == 0) {
                    flag_wait(&g_flags[FL_HE + (mtile * 2 + rank) * 8], 32);
                    fence_async_g();
#pragma unroll 1
                    for (int kb = 0; kb < 2; kb++)
                        tma_load_2d(sbase + kb * G2_HALF, &tmA2, smem_u32(&full2[kb]), kbase + g2_ord(kb) * BK, m0);
                }
                __syncwarp();
            }
        }
        if (warp >= 14) {
            bar_sync(7, 224);
#pragma unroll 1
            for (int cc = 0; cc < 2; cc++) {
                const int c = (warp - 14) * 2 + cc;
                const uint32_t urb = smem_u32(&S.ur[c * UR_PITCH]);
                const uint32_t vrb = smem_u32(&S.u.a.vr[c][0]);
                mbar_wait(smem_u32(&conv_bar[c]), 0);
#pragma unroll 1
                for (int ck = lane; ck < 193; ck += 32) {
                    float x[24];
#pragma unroll
                    for (int q = 0; q < 3; q++) {
                        const int rev = 2040 - 8 * (ck - 3 + q);
                        uint32_t w[4] = {0u, 0u, 0u, 0u};
                        if (rev < 2048)
                            asm volatile("ld.shared.v4.b32 {%0,%1,%2,%3}, [%4];" : "=r"(w[0]), "=r"(w[1]), "=r"(w[2]), "=r"(w[3])
                                         : "r"(urb + (uint32_t)((rev >> 6) * 128 + ((((rev >> 3) ^ (rev >> 6)) & 7) << 4))));
#pragma unroll
                        for (int i = 0; i < 4; i++) {
                            float2 f = __half22float2(*reinterpret_cast<__half2*>(&w[3 - i]));
                            x[8 * q + 2 * i] = f.y;
                            x[8 * q + 2 * i + 1] = f.x;
                        }
                    }
                    uint32_t wa[4], wb[4];
#pragma unroll
                    for (int i = 0; i < 4; i++) {
                        const int e = 2 * i;
                        const float m3 = x[e + 12] + x[e + 13];
                        __half2 ha = __floats2half2_rn(x[e + 11] + m3, m3 + x[e + 14]);
                        const float m5 = (x[e + 7] + x[e + 8]) + (x[e + 9] + x[e + 10]);
                        __half2 hb = __floats2half2_rn(x[e + 6] + m5, m5 + x[e + 11]);
                        wa[i] = *reinterpret_cast<uint32_t*>(&ha);
                        wb[i] = *reinterpret_cast<uint32_t*>(&hb);
                    }
                    const uint32_t o = (uint32_t)((ck ^ ((ck >> 3) & 1)) << 4);
                    asm volatile("st.shared.v4.b32 [%0], {%1,%2,%3,%4};" ::"r"(vrb + o), "r"(wa[0]), "r"(wa[1]), "r"(wa[2]), "r"(wa[3]) : "memory");
                    asm volatile("st.shared.v4.b32 [%0], {%1,%2,%3,%4};" ::"r"(vrb + 3104 + o), "r"(wb[0]), "r"(wb[1]), "r"(wb[2]), "r"(wb[3]) : "memory");
                }
            }
            __syncwarp();
            asm volatile("bar.arrive 10, 192;" ::: "memory");
            mbar_wait(smem_u32(&tail_bar), 0);
#pragma unroll 1
            for (int it = 0; it < 8; it++) {
                const int c = (warp - 14) * 2 + (it >> 2), ck = (it & 3) * 32 + lane;
                const uint32_t urb = smem_u32(&S.ur[c * UR_PITCH]);
                float P[28];
                P[4] = 0.f;
#pragma unroll
                for (int q = 0; q < 4; q++) {
                    const int rev = 2040 - 8 * (ck - 3 + q);
                    uint32_t w[4] = {0u, 0u, 0u, 0u};
                    if (rev < 2048)
                        asm volatile("ld.shared.v4.b32 {%0,%1,%2,%3}, [%4];" : "=r"(w[0]), "=r"(w[1]), "=r"(w[2]), "=r"(w[3])
                                     : "r"(urb + (uint32_t)((rev >> 6) * 128 + ((((rev >> 3) ^ (rev >> 6)) & 7) << 4))));
#pragma unroll
                    for (int i = 0; i < 4; i++) {
                        const int j = 8 * q + 2 * i;
                        float2 f = __half22float2(*reinterpret_cast<__half2*>(&w[3 - i]));
                        if (j >= 4 && j < 27) P[j + 1] = P[j] + f.y;
                        if (j + 1 >= 4 && j + 1 < 27) P[j + 2] = P[j + 1] + f.x;
                    }
                }
                uint32_t wa[4], wb[4];
#pragma unroll
                for (int i = 0; i < 4; i++) {
                    const int e = 2 * i;
                    __half2 ha = __floats2half2_rn(P[e + 20] - P[e + 13], P[e + 21] - P[e + 14]);
                    __half2 hb = __floats2half2_rn(P[e + 13] - P[e + 4], P[e + 14] - P[e + 5]);
                    wa[i] = *reinterpret_cast<uint32_t*>(&ha);
                    wb[i] = *reinterpret_cast<uint32_t*>(&hb);
                }
                const uint32_t o = sbase + V3_OFF + c * 4096 + (uint32_t)((ck ^ ((ck >> 3) & 1)) << 4);
                asm volatile("st.shared.v4.b32 [%0], {%1,%2,%3,%4};" ::"r"(o), "r"(wa[0]), "r"(wa[1]), "r"(wa[2]), "r"(wa[3]) : "memory");
                asm volatile("st.shared.v4.b32 [%0], {%1,%2,%3,%4};" ::"r"(o + 2048), "r"(wb[0]), "r"(wb[1]), "r"(wb[2]), "r"(wb[3]) : "memory");
            }
            __syncwarp();
            asm volatile("bar.arrive 11, 192;" ::: "memory");
            if (threadIdx.x == 448) TS(7, 10);
        }
        cluster_wait();
        cluster_arrive();
    } else {
        KgenIn kin;
        if (warp >= 8) kin = kgen_load(logAr, Aim, Cre, Cim, logdt, blockIdx.x * CONV_CH + (warp & 3));
        if (threadIdx.x == 256) TS(3, 0);
        if (threadIdx.x == 0) { TS(4, 0); TS(2, 0); }
        if (warp < 8) ln_block(xin, sbase, smem_u32(&S.ur[0]), blockIdx.x);
        if (warp < 4) {
            if (threadIdx.x == 0) TS(7, 6);
            ln_block2(smem_u32(&S.ur[0]), sbase + 2 * G1_STAGE, ((L_SEQ - 16 - blockIdx.x * 16) >> 6) & 1);
            if (threadIdx.x == 0) TS(7, 7);
            fence_async_s();
            __syncwarp();
            asm volatile("bar.arrive 2, 160;" ::: "memory");
            if (threadIdx.x == 0) TS(7, 0);
        }
        float inv_sc = 1.0f;
        if (warp >= 8) inv_sc = kgen_warp(kin, &S.u.T[warp & 3][0], &S.kh[warp & 3][0], 0, 5);

    if (warp < 8) {
        const int wg = warp >> 2;
        asm volatile("setmaxnreg.inc.sync.aligned.u32 168;");
        if (warp == 1 && lane < G1_BN / 8)
            reinterpret_cast<uint4*>(sbias)[lane] = reinterpret_cast<const uint4*>(bias1 + n0)[lane];
        {
            float acc[112];
            bar_sync(8, 288);
            for (int kb = 0; kb < NKB1; kb++) {
                int s = kb % G1_ST;
                uint32_t ph = (kb / G1_ST) & 1;
                mbar_wait(smem_u32(&full1[s]), ph);
                if (threadIdx.x == 0 && kb == 0) TS(1, 1);
                if (threadIdx.x == 0 && kb == 4) TS(1, 2);
                uint32_t sa = sbase + s * G1_STAGE + wg * (64 * 128);
                uint32_t sb = sbase + s * G1_STAGE + BM * BK * 2;
                wgmma_fence();
#pragma unroll
                for (int kk = 0; kk < 4; kk++) {
                    uint64_t da = make_desc(sa + kk * 32, 16, 1024);
                    uint64_t db = make_desc(sb + kk * 2048, BK * 128, 1024);
                    uint64_t db2 = make_desc(sb + 2 * (BK * 128) + kk * 2048, BK * 128, 1024);
                    wgmma_n128p(acc, da, db, (kb | kk) != 0);
                    wgmma_n96p(acc + 64, da, db2, (kb | kk) != 0);
                }
                wgmma_commit();
                if (kb > 0) {
                    wgmma_wait<1>();
                    const int ps = (kb - 1) % G1_ST;
                    if ((threadIdx.x & 127) == 0) mbar_arrive(smem_u32(&empty1[ps]));
                }
            }
            wgmma_wait<0>();
            if ((threadIdx.x & 127) == 0) mbar_arrive(smem_u32(&empty1[(NKB1 - 1) % G1_ST]));
            if (threadIdx.x == 0) TS(1, 3);
            bar_sync(5, 256);
            const int t4 = lane & 3;
            const uint32_t ste = sbase + warp * 3072;
            const uint32_t stg = sbase + 32768 + warp * 4096;
            const int srow = (lane & 7) + 8 * ((lane >> 3) & 1), shalf = lane >> 4;
            const __nv_bfloat162 zero2 = __floats2bfloat162_rn(0.f, 0.f);
#pragma unroll
            for (int np = 0; np < G1_BN / 16; np++) {
                uint32_t r[4];
#pragma unroll
                for (int i = 0; i < 4; i++) {
                    const int nb = 2 * np + (i >> 1);
                    __nv_bfloat162 bb = *reinterpret_cast<const __nv_bfloat162*>(&sbias[nb * 8 + 2 * t4]);
                    __nv_bfloat162 v = __floats2bfloat162_rn(acc[nb * 4 + (i & 1) * 2], acc[nb * 4 + (i & 1) * 2 + 1]);
                    v = __hmax2(__hadd2(v, bb), zero2);
                    v = __hmul2(v, v);
                    r[i] = *reinterpret_cast<uint32_t*>(&v);
                }
                const int ch = 2 * (np < 6 ? np & 3 : (np - 6) & 3) + shalf;
                const uint32_t ad = np < 4 ? ste + srow * 128 + ((ch ^ (srow & 7)) << 4)
                                  : np < 6 ? ste + 2048 + srow * 64 + ((ch ^ ((srow >> 1) & 3)) << 4)
                                           : stg + ((np - 6) >> 2) * 2048 + srow * 128 + ((ch ^ (srow & 7)) << 4);
                asm volatile("stmatrix.sync.aligned.m8n8.x4.shared.b16 [%0], {%1,%2,%3,%4};"
                             ::"r"(ad), "r"(r[0]), "r"(r[1]), "r"(r[2]), "r"(r[3]) : "memory");
                if (np == 5) {
                    fence_async_s();
                    asm volatile("bar.arrive 12, 288;" ::: "memory");
                }
            }
            fence_async_s();
            __syncwarp();
            if (threadIdx.x == 0) TS(1, 4);
            if (lane == 0) {
                const int row0 = m0 + wg * 64 + (warp & 3) * 16;
#pragma unroll
                for (int j = 0; j < 2; j++) tma_store_2d(&tmH64, stg + j * 2048, n0 + 96 + j * 64, row0);
                bulk_commit();
                bulk_wait<0>();
            }
            __syncwarp();
            asm volatile("bar.arrive 4, 288;" ::: "memory");
            if (lane == 0) flag_add(&g_flags[FL_H + (mtile * 2 + (jt >> 2)) * 8]);
            __syncwarp();
            if (threadIdx.x == 0) TS(1, 5);
        }
        float acc[64];
        const int row0 = m0 + wg * 64 + (warp & 3) * 16;
        const int ncol0 = n2 + rank * 64;
        uint4 xv[4], nv[4];
#pragma unroll
        for (int rr = 0; rr < 4; rr++) {
            int r = rr * 4 + (lane >> 3);
            size_t off = (size_t)(row0 + r) * D_MODEL + ncol0 + (lane & 7) * 8;
            xv[rr] = *reinterpret_cast<const uint4*>(xin + off);
            nv[rr] = __ldcg(reinterpret_cast<const uint4*>(g_xn + off));
        }
        const uint4 dv = *reinterpret_cast<const uint4*>(dskip + ncol0 + (lane & 7) * 8);
        const int g = lane >> 2, t4 = lane & 3;
        __nv_bfloat162 bb[8];
#pragma unroll
        for (int nb = 0; nb < 8; nb++) bb[nb] = *reinterpret_cast<const __nv_bfloat162*>(bias2 + ncol0 + nb * 8 + 2 * t4);
        cluster_wait();
        bar_sync(9, 384);
        for (int kb = 0; kb < NKB2; kb++) {
            int s = kb % G2_ST;
            uint32_t ph = (kb / G2_ST) & 1;
            mbar_wait(smem_u32(&full2[s]), ph);
            if (threadIdx.x == 0 && kb == 0) TS(2, 1);
            if (threadIdx.x == 0 && kb == 7) TS(2, 2);
            uint32_t sa = sbase + g2_a(s) + wg * (64 * 128);
            uint32_t sb = sbase + g2_b(s);
            wgmma_fence();
#pragma unroll
            for (int kk = 0; kk < 4; kk++) {
                uint64_t da = make_desc(sa + kk * 32, 16, 1024);
                uint64_t db = make_desc(sb + kk * 2048, BK * 128, 1024);
                wgmma_m64n128k16(acc, da, db, (kb | kk) != 0);
            }
            wgmma_commit();
            if (kb > 0) {
                wgmma_wait<1>();
                const int ps = (kb - 1) % G2_ST;
                if ((threadIdx.x & 127) == 0) mbar_arrive(smem_u32(&empty2[ps]));
            }
        }
        wgmma_wait<0>();
        if (threadIdx.x == 0) TS(2, 3);
        unsigned char* recvp = warp < 6 ? &S.u.a.db[0][0] + warp * 4096
                                        : reinterpret_cast<unsigned char*>(&S.u.a.ylow[0]) + (warp - 6) * 4096;
        {
            uint32_t rdst, rbar;
            asm volatile("mapa.shared::cluster.u32 %0, %1, %2;" : "=r"(rdst) : "r"(smem_u32(recvp) + lane * 16), "r"(rank ^ 1));
            asm volatile("mapa.shared::cluster.u32 %0, %1, %2;" : "=r"(rbar) : "r"(smem_u32(&recv_bar[warp])), "r"(rank ^ 1));
            mbar_wait(smem_u32(&ready_bar), 0);
            if (rank == 0) {
#pragma unroll
                for (int i = 0; i < 8; i++)
                    asm volatile("st.async.weak.shared::cluster.mbarrier::complete_tx::bytes.v4.f32 [%0], {%1,%2,%3,%4}, [%5];"
                                 ::"r"(rdst + i * 512), "f"(acc[32 + 4 * i]), "f"(acc[32 + 4 * i + 1]), "f"(acc[32 + 4 * i + 2]),
                                   "f"(acc[32 + 4 * i + 3]), "r"(rbar) : "memory");
            } else {
#pragma unroll
                for (int i = 0; i < 8; i++)
                    asm volatile("st.async.weak.shared::cluster.mbarrier::complete_tx::bytes.v4.f32 [%0], {%1,%2,%3,%4}, [%5];"
                                 ::"r"(rdst + i * 512), "f"(acc[4 * i]), "f"(acc[4 * i + 1]), "f"(acc[4 * i + 2]),
                                   "f"(acc[4 * i + 3]), "r"(rbar) : "memory");
#pragma unroll
                for (int i = 0; i < 32; i++) acc[i] = acc[32 + i];
            }
        }
        if (threadIdx.x == 0) TS(2, 4);
        mbar_wait(smem_u32(&recv_bar[warp]), 0);
        __syncwarp();
        cluster_arrive();
        if (threadIdx.x == 0) TS(2, 5);
        {
            const float4* part = reinterpret_cast<const float4*>(recvp) + lane;
#pragma unroll
            for (int i = 0; i < 8; i++) {
                float4 v = part[i * 32];
                acc[4 * i] += v.x; acc[4 * i + 1] += v.y; acc[4 * i + 2] += v.z; acc[4 * i + 3] += v.w;
            }
            __syncwarp();
            unsigned char* stg = recvp;
#pragma unroll
            for (int nb = 0; nb < 8; nb++) {
                int col = nb * 8 + 2 * t4;
#pragma unroll
                for (int hh = 0; hh < 2; hh++) {
                    __nv_bfloat162 v = __hadd2(__floats2bfloat162_rn(acc[nb * 4 + hh * 2], acc[nb * 4 + hh * 2 + 1]), bb[nb]);
                    float2 vf = __bfloat1622float2(v);
                    float g0 = __fdividef(vf.x, 1.0f + __expf(-vf.x));
                    float g1 = __fdividef(vf.y, 1.0f + __expf(-vf.y));
                    *reinterpret_cast<__nv_bfloat162*>(stg + (g + hh * 8) * G2_EPITCH + col * 2) =
                        __floats2bfloat162_rn(g0, g1);
                }
            }
            mbar_wait(smem_u32(&y_bar), 0);
            __syncwarp();
            if (threadIdx.x == 0) TS(2, 7);
            uint4 yv[4];
#pragma unroll
            for (int rr = 0; rr < 4; rr++) {
                int r = rr * 4 + (lane >> 3);
                const unsigned char* yp0 = &S.ur[(lane & 7) * (2 * YT_PITCH) + (warp * 16 + r) * 8];
                uint2 y0 = *reinterpret_cast<const uint2*>(yp0);
                uint2 y1 = *reinterpret_cast<const uint2*>(yp0 + YT_PITCH);
                yv[rr] = make_uint4(y0.x, y0.y, y1.x, y1.y);
            }
#pragma unroll
            for (int rr = 0; rr < 4; rr++) {
                int r = rr * 4 + (lane >> 3);
                int cc = (lane & 7) * 8;
                uint4 gv = *reinterpret_cast<const uint4*>(stg + r * G2_EPITCH + cc * 2);
                size_t off = (size_t)(row0 + r) * D_MODEL + ncol0 + cc;
                uint4 ov;
                const __nv_bfloat162* gp = reinterpret_cast<const __nv_bfloat162*>(&gv);
                const __nv_bfloat162* yp = reinterpret_cast<const __nv_bfloat162*>(&yv[rr]);
                const __nv_bfloat162* xp = reinterpret_cast<const __nv_bfloat162*>(&xv[rr]);
                const __nv_bfloat162* np = reinterpret_cast<const __nv_bfloat162*>(&nv[rr]);
                const __nv_bfloat162* dp = reinterpret_cast<const __nv_bfloat162*>(&dv);
                __nv_bfloat162* op = reinterpret_cast<__nv_bfloat162*>(&ov);
#pragma unroll
                for (int e = 0; e < 4; e++) {
                    __nv_bfloat162 sv = __hadd2(yp[e], __hmul2(np[e], dp[e]));
                    op[e] = __hadd2(xp[e], __hmul2(sv, gp[e]));
                }
                *reinterpret_cast<uint4*>(out + off) = ov;
            }
            if ((threadIdx.x & 127) == 0) TS(2, 6);
        }
    } else {
        const int tid = threadIdx.x - 256;
        const int c = tid >> 5;
        const int g = lane >> 2, t4 = lane & 3;
        if (tid == 0) TS(3, 8);
        cluster_wait();
        cluster_arrive();
        if (lane == 0) sinv[c] = inv_sc;
        bar_sync(7, 224);
        kexpand_warp(&S.kh[c][0], reinterpret_cast<__half*>(&S.u.a.db[c][0]));
        if (tid == 0) TS(3, 9);
        mbar_wait(smem_u32(&conv_bar[c]), 0);
        for (int i = lane; i < 72; i += 32)
            *reinterpret_cast<uint4*>(&S.ur[c * UR_PITCH + 4096 + i * 16]) = make_uint4(0, 0, 0, 0);
        fence_async_s();
        __syncwarp();
        const uint32_t urb = smem_u32(&S.ur[c * UR_PITCH]);
        const uint32_t vrb = smem_u32(&S.u.a.vr[c][0]);
        bar_sync(6, 128);
        if (tid == 0) TS(3, 1);
        {
            const uint32_t kpa0 = smem_u32(&S.u.a.db[0][0]) + (uint32_t)(((g & 1) ? KPO_OFF : 0) + 2 * t4 + (g & ~1) + 16 * c) * 2;
            const uint64_t db0 = make_desc(smem_u32(&S.ur[0]), 16, 1024);
            auto ldk = [&](uint32_t a) { uint32_t v; asm volatile("ld.shared.b32 %0, [%1];" : "=r"(v) : "r"(a)); return v; };
            float acc[2][16];
            auto depi = [&](int ch, const float* ac) {
                float* dbuf = reinterpret_cast<float*>(&S.u.a.db[ch][0]);
                const float sc = sinv[ch];
#pragma unroll
                for (int i = 0; i < 16; i++) {
                    const int np = (i >> 2) * 8 + 2 * t4 + (i & 1), m = 16 * c + g + ((i & 2) ? 8 : 0);
                    if (i < 12) {
                        const int x = 64 * (23 - np) + m;
                        dbuf[x + (x >> 7) * 8] = ac[i];
                    } else {
                        const int l = 64 * (31 - np) + m;
                        S.u.a.ylow[l * CONV_CH + (l >> 7) * YS_PAD + ch] = __float2bfloat16_rn(ac[i] * sc);
                    }
                }
            };
#pragma unroll
            for (int i = 0; i < CONV_CH; i++) mbar_wait(smem_u32(&conv_bar[i]), 0);
#pragma unroll
            for (int ch = 0; ch < CONV_CH; ch++) {
                const uint32_t kpa = kpa0 + ch * DB_BYTES;
#pragma unroll
                for (int k0 = 0; k0 < 37; k0 += 4) {
                    uint32_t Pl[5], Ph[4];
#pragma unroll
                    for (int i = 0; i <= 4; i++) if (k0 + i <= 37) Pl[i] = ldk(kpa + (k0 + i) * 32);
#pragma unroll
                    for (int i = 0; i < 4; i++) if (k0 + i < 37) Ph[i] = ldk(kpa + (k0 + i) * 32 + 16);
                    if (k0 > 0 || ch > 0) wgmma_wait<1>();
                    wgmma_fence();
#pragma unroll
                    for (int i = 0; i < 4; i++) {
                        const int ks = k0 + i;
                        if (ks < 37)
                            wgmma_rs32h(acc[ch & 1], Pl[i], Ph[i], Ph[i], Pl[i + 1],
                                        db0 + (uint64_t)((ch * UR_PITCH + (ks >> 2) * 128 + (ks & 3) * 32) >> 4), ks != 0);
                    }
                    wgmma_commit();
                    if (k0 == 4 && ch > 0) {
                        bar_sync(6, 128);
                        depi(ch - 1, acc[(ch - 1) & 1]);
                    }
                }
            }
            bar_sync(6, 128);
            wgmma_wait<0>();
            depi(CONV_CH - 1, acc[(CONV_CH - 1) & 1]);
        }
        if (tid == 0) TS(3, 7);
        const int lm = lane >> 3, lr = lane & 7;
        float* cbuf = reinterpret_cast<float*>(&S.u.a.db[c][0]);
        {
            const unsigned short* khs = reinterpret_cast<const unsigned short*>(&S.kh[c][0]);
            float accL[6][2][4];
#pragma unroll
            for (int i = 0; i < 6; i++)
#pragma unroll
                for (int h = 0; h < 2; h++)
#pragma unroll
                    for (int k = 0; k < 4; k++) accL[i][h][k] = 0.f;
            const int cb0 = 2 * (8 * (lm & 1) + lr) + (lm >> 1);
            const uint32_t bo0 = (uint32_t)((cb0 ^ ((cb0 >> 3) & 1)) << 4);
            const uint32_t bo1 = (uint32_t)(((cb0 + 1) ^ (((cb0 + 1) >> 3) & 1)) << 4);
            bar_sync(10, 192);
#pragma unroll 1
            for (int sp = 1; sp <= 4; sp++)
                level_set<2, 3>(accL, khs, 256 + sp, 4, 63, vrb + ((sp & 1) ? 0 : 3104) + (sp <= 2 ? bo1 : bo0));
            if (tid == 0) TS(3, 10);
            bar_sync(11, 192);
#pragma unroll 1
            for (int sp = 1; sp <= 2; sp++)
                level_set<4, 4>(accL, khs, 384 + sp, 2, 127, sbase + V3_OFF + c * 4096 + (sp - 1) * 2048 + bo0);
            asm volatile("bar.arrive 9, 384;" ::: "memory");
            __syncwarp();
            if (lane == 0) mbar_arrive(smem_u32(&lv_bar));
            if (tid == 0) TS(3, 11);
            bar_sync(6, 128);
#pragma unroll
            for (int i = 0; i < 6; i++)
#pragma unroll
                for (int h = 0; h < 2; h++)
#pragma unroll
                    for (int e = 0; e < 2; e++) {
                        const int x = 256 * i + 16 * (g + 8 * e) + 8 * h + 2 * t4;
                        float2* p = reinterpret_cast<float2*>(&cbuf[x + (x >> 7) * 8]);
                        float2 v = *p;
                        *p = make_float2((v.x + accL[i][h][2 * e]) * inv_sc, (v.y + accL[i][h][2 * e + 1]) * inv_sc);
                    }
        }
        bar_sync(6, 128);
        if (tid == 0) TS(3, 6);
        {
            uint4 yo[6];
#pragma unroll
            for (int it = 0; it < 6; it++) {
                const int x = it * 256 + 2 * tid;
                float2 v[4];
#pragma unroll
                for (int ch = 0; ch < 4; ch++) v[ch] = *reinterpret_cast<const float2*>(&S.u.a.db[ch][(x + (x >> 7) * 8) * 4]);
                if (it >= 2) {
                    uint32_t uo[3];
#pragma unroll
                    for (int i = 0; i < 3; i++) {
                        const int rev = 2047 - (x - 516 + i);
                        uo[i] = (uint32_t)((rev >> 6) * 128 + ((((rev >> 3) ^ (rev >> 6)) & 7) << 4) + (rev & 7) * 2);
                    }
#pragma unroll
                    for (int ch = 0; ch < 4; ch++) {
                        const float kk = __half2float(S.kh[ch][512]) * sinv[ch];
                        const float u0 = __half2float(*reinterpret_cast<const __half*>(&S.ur[ch * UR_PITCH + uo[0]]));
                        const float u1 = __half2float(*reinterpret_cast<const __half*>(&S.ur[ch * UR_PITCH + uo[1]]));
                        const float u2 = __half2float(*reinterpret_cast<const __half*>(&S.ur[ch * UR_PITCH + uo[2]]));
                        v[ch].x = fmaf(kk, u0 + u1, v[ch].x);
                        v[ch].y = fmaf(kk, u1 + u2, v[ch].y);
                    }
                }
                __nv_bfloat162 o0 = __floats2bfloat162_rn(v[0].x, v[1].x), o1 = __floats2bfloat162_rn(v[2].x, v[3].x);
                __nv_bfloat162 o2 = __floats2bfloat162_rn(v[0].y, v[1].y), o3 = __floats2bfloat162_rn(v[2].y, v[3].y);
                yo[it] = make_uint4(*reinterpret_cast<uint32_t*>(&o0), *reinterpret_cast<uint32_t*>(&o1),
                                    *reinterpret_cast<uint32_t*>(&o2), *reinterpret_cast<uint32_t*>(&o3));
            }
            bar_sync(6, 128);
#pragma unroll
            for (int it = 0; it < 6; it++) *reinterpret_cast<uint4*>(&S.u.a.db[0][0] + (it * 256 + 2 * tid) * 8) = yo[it];
        }
        if (tid == 0) TS(3, 2);
        fence_async_s();
        bar_sync(6, 128);
        if (tid < 16) {
            const uint32_t src = tid < 4 ? smem_u32(&S.u.a.ylow[tid * (128 * CONV_CH + YS_PAD)]) : smem_u32(&S.u.a.db[0][0]) + (tid - 4) * 1024;
            bulk_store(g_s + ((size_t)blockIdx.x * L_SEQ + tid * 128) * CONV_CH, src, 128 * CONV_CH * 2);
            bulk_commit();
            bulk_wait<0>();
        }
        __syncwarp();
        if (tid == 0) mbar_arrive_cluster(smem_u32(&ready_bar), rank ^ 1);
        if (tid < 16) flag_add(&g_flags[FL_Y + (blockIdx.x >> 4) * 8]);
        if (tid == 0) {
            TS(3, 4);
            flag_wait(&g_flags[FL_Y + jt * 8], 256);
        }
        __syncwarp();
        if (tid < 16) fence_async_g();
        if (tid < 16)
            asm volatile("cp.async.bulk.shared::cluster.global.mbarrier::complete_tx::bytes [%0], [%1], %2, [%3];"
                         ::"r"(smem_u32(&S.ur[tid * YT_PITCH])), "l"(g_s + ((size_t)(jt * 16 + tid) * L_SEQ + m0) * CONV_CH),
                           "r"(1024), "r"(smem_u32(&y_bar)) : "memory");
    }
    }
    __syncwarp();
    cluster_wait();
    __syncthreads();
    if (threadIdx.x == 0) {
        unsigned old = atomicAdd(&g_flags[FL_DONE], 1u);
        if (old == gridDim.x - 1) {
            for (int i = 0; i < FL_TOT; i += 8) g_flags[i] = 0u;
        }
    }
}

typedef CUresult (*PFN_encodeTiled)(CUtensorMap*, CUtensorMapDataType, cuuint32_t, void*, const cuuint64_t*,
                                    const cuuint64_t*, const cuuint32_t*, const cuuint32_t*, CUtensorMapInterleave,
                                    CUtensorMapSwizzle, CUtensorMapL2promotion, CUtensorMapFloatOOBfill);

static void make_map(PFN_encodeTiled enc, CUtensorMap* tm, void* ptr, uint64_t inner, uint64_t outer, uint32_t box_in,
                     uint32_t box_out, CUtensorMapSwizzle sw = CU_TENSOR_MAP_SWIZZLE_128B) {
    cuuint64_t dims[2] = {inner, outer};
    cuuint64_t strides[1] = {inner * 2};
    cuuint32_t box[2] = {box_in, box_out};
    cuuint32_t es[2] = {1, 1};
    enc(tm, CU_TENSOR_MAP_DATA_TYPE_BFLOAT16, 2, ptr, dims, strides, box, es, CU_TENSOR_MAP_INTERLEAVE_NONE,
        sw, CU_TENSOR_MAP_L2_PROMOTION_L2_256B, CU_TENSOR_MAP_FLOAT_OOB_FILL_NONE);
}

extern "C" void kernel_launch(void* const* d_in, const int* in_sizes, int n_in, void* d_out, int out_size) {
    const __nv_bfloat16* u = (const __nv_bfloat16*)d_in[0];
    const __nv_bfloat16* logAr = (const __nv_bfloat16*)d_in[1];
    const __nv_bfloat16* Aim = (const __nv_bfloat16*)d_in[2];
    const __nv_bfloat16* Cre = (const __nv_bfloat16*)d_in[3];
    const __nv_bfloat16* Cim = (const __nv_bfloat16*)d_in[4];
    const __nv_bfloat16* logdt = (const __nv_bfloat16*)d_in[5];
    const __nv_bfloat16* Dskip = (const __nv_bfloat16*)d_in[6];
    const __nv_bfloat16* w1 = (const __nv_bfloat16*)d_in[8];
    const __nv_bfloat16* b1 = (const __nv_bfloat16*)d_in[9];
    const __nv_bfloat16* w2 = (const __nv_bfloat16*)d_in[10];
    const __nv_bfloat16* b2 = (const __nv_bfloat16*)d_in[11];
    __nv_bfloat16* out = (__nv_bfloat16*)d_out;

    static PFN_encodeTiled enc = nullptr;
    static void *p_xn = nullptr, *p_h = nullptr, *p_ur = nullptr;
    if (!enc) {
        void* fn = nullptr;
        cudaDriverEntryPointQueryResult st;
        cudaGetDriverEntryPoint("cuTensorMapEncodeTiled", &fn, cudaEnableDefault, &st);
        enc = (PFN_encodeTiled)fn;
        cudaGetSymbolAddress(&p_xn, g_xn);
        cudaGetSymbolAddress(&p_h, g_h);
        cudaGetSymbolAddress(&p_ur, g_ur);
    }
    CUtensorMap tmA1, tmB1, tmA2, tmB2, tmUR, tmH64, tmH32;
    make_map(enc, &tmUR, p_ur, UR_REAL, D_MODEL, 16, 256, CU_TENSOR_MAP_SWIZZLE_NONE);
    make_map(enc, &tmH64, p_h, F_HID, L_SEQ, 64, 16);
    make_map(enc, &tmH32, p_h, F_HID, L_SEQ, 32, 16, CU_TENSOR_MAP_SWIZZLE_64B);
    make_map(enc, &tmA1, p_xn, D_MODEL, L_SEQ, 64, 128);
    make_map(enc, &tmB1, (void*)w1, F_HID, D_MODEL, 64, 64);
    make_map(enc, &tmA2, p_h, F_HID, L_SEQ, 64, 128);
    make_map(enc, &tmB2, (void*)w2, D_MODEL, F_HID, 64, 64);

    cudaStream_t st = cudaStreamPerThread;
    static bool attr_done = false;
    if (!attr_done) {
        cudaFuncSetAttribute(mega_kernel, cudaFuncAttributeMaxDynamicSharedMemorySize, KB_SMEM);
        attr_done = true;
    }
    mega_kernel<<<128, 512, KB_SMEM, st>>>(tmA1, tmB1, tmA2, tmB2, tmUR, tmH64, tmH32, u, b1, b2, Dskip, logAr, Aim, Cre, Cim, logdt, out, w1, w2);
}
```
